```python
import torch

def _softmax(x, axis=-1):
    return torch.softmax(x, dim=axis)
def _gelu(x):
    return torch.nn.functional.gelu(x, approximate="tanh")
def _silu(x):
    return torch.nn.functional.silu(x)
def _sigmoid(x):
    return torch.sigmoid(x)
def _layernorm(x, axis=-1, eps=1e-5):
    m = x.mean(dim=axis, keepdim=True)
    v = x.var(dim=axis, keepdim=True, unbiased=False)
    return (x - m) / torch.sqrt(v + eps)
def _scatter_add(tgt, idx, src, axis=0):
    return tgt.clone().index_add_(axis, idx, src)
def _segment_sum(src, seg, n):
    out = torch.zeros((n,) + src.shape[1:], dtype=src.dtype)
    return out.index_add_(0, seg, src)
def _pad(x, pw):
    flat = tuple(v for pair in reversed(pw) for v in pair)
    return torch.nn.functional.pad(x, flat)

kernel_name = 'sequential_preLN__sliding_local_dilated__moe_arch_mod__prompt'

def setup_inputs():

    _w = (lambda a: (lambda t: t.to(torch.bfloat16) if t.is_floating_point() else t)(torch.as_tensor(a)))
    def _A_setup():
        B, S, D = 1, 2048, 640
        return {
            "x": _w((lambda *s: torch.randn(*s, dtype=torch.bfloat16) * 0.05)(B, S, D)),
            "wqkv": _w((lambda *s: torch.randn(*s, dtype=torch.bfloat16) * 0.05)(D, 3 * D)),
            "wo": _w((lambda *s: torch.randn(*s, dtype=torch.bfloat16) * 0.05)(D, D)),
        }
    _A_in = _A_setup()

    def _B_setup():
        B, S, D, F, C = 1, 2048, 640, 1536, 1
        return {
            "x": _w((lambda *s: torch.randn(*s, dtype=torch.bfloat16) * 0.05)(B, S, D)),
            "w_r": _w((lambda *s: torch.randn(*s, dtype=torch.bfloat16) * 0.05)(D)),
            "w_gate": _w((lambda *s: torch.randn(*s, dtype=torch.bfloat16) * 0.05)(D, F)),
            "w_up": _w((lambda *s: torch.randn(*s, dtype=torch.bfloat16) * 0.05)(D, F)),
            "w_down": _w((lambda *s: torch.randn(*s, dtype=torch.bfloat16) * 0.05)(F, D)),
        }
    _B_in = _B_setup()

    return {
        "A_x": _A_in["x"],
        "A_wqkv": _A_in["wqkv"],
        "A_wo": _A_in["wo"],
        "B_x": _B_in["x"],
        "B_w_r": _B_in["w_r"],
        "B_w_gate": _B_in["w_gate"],
        "B_w_up": _B_in["w_up"],
        "B_w_down": _B_in["w_down"],
    }

def reference(A_x, A_wqkv, A_wo, B_x, B_w_r, B_w_gate, B_w_up, B_w_down):
    def _A_ref(x, wqkv, wo):
        B, S, D = x.shape
        H = 32; Dh = D // H
        W, dil = 8, 2
        qkv = (lambda x, *d: x.permute(*d))((x @ wqkv).reshape(B, S, 3, H, Dh), 2, 0, 3, 1, 4)
        q, k, v = qkv[0], qkv[1], qkv[2]
        scale = Dh ** -0.5
        pos = torch.arange(S)
        off = torch.arange(W) * dil
        idx = pos[:, None] - off[None, :]
        mask = idx >= 0
        idx_c = torch.where(mask, idx, 0).reshape(-1)
        kg = k[:, :, idx_c, :].reshape(B, H, S, W, Dh)
        vg = v[:, :, idx_c, :].reshape(B, H, S, W, Dh)
        logits = torch.einsum("bhsd,bhswd->bhsw", q, kg) * scale
        logits = torch.where(mask[None, None, :, :], logits, -1e9)
        attn = _softmax(logits, axis=-1)
        o = torch.einsum("bhsw,bhswd->bhsd", attn, vg)
        return (lambda x, *d: x.permute(*d))(o, 0, 2, 1, 3).reshape(B, S, D) @ wo

    def _B_ref(x, w_r, w_gate, w_up, w_down):
        B, S, D = x.shape
        C = 1
        r = x @ w_r
        idx = torch.argsort(-r, axis=-1)[:, :C]
        idx_e = (lambda x, n, axis: torch.repeat_interleave(x, n, dim=axis))(idx.reshape(B, C, 1), D, axis=2)
        x_sel = (lambda x, i, axis: torch.take_along_dim(x, i, dim=axis))(x, idx_e, axis=1)
        g = _silu(x_sel @ w_gate)
        u = x_sel @ w_up
        y = (g * u) @ w_down
        r_sel = _sigmoid((lambda x, i, axis: torch.take_along_dim(x, i, dim=axis))(r, idx, axis=1))
        y = y * r_sel.reshape(B, C, 1)
        b_off = (torch.arange(B) * S).reshape(B, 1)
        flat_idx = (idx + b_off).reshape(B * C)
        zero = (x * 0.0).reshape(B * S, D)
        upd = _scatter_add(zero, flat_idx, y.reshape(B * C, D), axis=0)
        return x + upd.reshape(B, S, D)

    x = A_x
    h = x + _A_ref(_layernorm(x, axis=-1), A_wqkv, A_wo)
    h2 = h + _B_ref(_layernorm(h, axis=-1), B_w_r, B_w_gate, B_w_up, B_w_down)
    return h2
```

```cpp
#include <cuda_runtime.h>
#include <cuda_bf16.h>
#include <cuda.h>
#include <stdint.h>
#include <stdio.h>

namespace {

constexpr int kStage = 47104;
constexpr int kWo = 0;
constexpr int kKst = 81920;
constexpr int kVst = 92160;
constexpr int kUp = 116736;
constexpr int kDown = 141312;
constexpr int kOutSt = 161792;
constexpr int kPart = 184320;
constexpr int kSel = 185344;
constexpr int kGate = 188416;
constexpr int kUpSide = kGate + 12288;
constexpr int kWoTail = 208896;
constexpr int kBars = 229376;
constexpr int kStat = kBars + 128;
constexpr int kBext = kStat + 1152;
constexpr int kMisc = kBext + 1152;
constexpr int kProf = kMisc + 48;
constexpr int kSmemBytes = 232448;
constexpr int kPitch = 176;
enum { B_FULL = 0, B_EMPTY = 4, B_AUX = 8, B_WO = 9, B_FFN = 10, B_TAIL = 11, B_HALF = 12 };
enum { NB_TURN = 1, NB_OL = 7, NB_WG = 3, NB_GRID = 5, NB_RED = 6, NB_KV = 8, NB_KEY = 1 };

struct __align__(128) Scratch {
  uint4 obuf[16][8][5][8][32];
  uint4 cand[128][8][3][4];
  uint4 halo0[2][8][5][32];
  uint4 halo[14][8][5][32];
  uint4 stat1[1024];
  uint4 cs[8][64];
  uint32_t hint[2][16][32];
  uint32_t keys[32];
  uint4 base[8][10];
  uint4 pad1[168];
  uint4 stat2[16][8][8][16];
  uint4 pad2[512];
  uint4 ypart[96][192];
};
constexpr int kReset1 = 13, kReset2 = 24, kReset = 36;
static_assert(offsetof(Scratch, stat2) == offsetof(Scratch, halo) + 1536 * 16 * kReset1 && sizeof(Scratch) == offsetof(Scratch, halo) + 1536 * 16 * kReset, "even split");

__device__ Scratch g_scr;
__device__ unsigned g_count[128];
#define PROF(i)
#define PROF2(i, v)
#define PROFG(i)

struct Params {
  const uint8_t* x;
  const uint8_t* wqkv;
  uint4* scr;
  uint8_t* out;
  const uint32_t* wr;
  unsigned* count;
  const uint8_t *wo, *wgate, *wup, *wdown;
  CUtensorMap mx, mw64, mw16, mwo, mtail, mgate, mup, mdown;
};

constexpr int kSpin = 1 << 14;
__device__ __forceinline__ void pin(uint32_t& v) { asm volatile("" : "+r"(v)); }
__device__ __forceinline__ void pin(float& v) { asm volatile("" : "+f"(v)); }
template <class T> __device__ __forceinline__ void pin(T*& v) { asm volatile("" : "+l"(v)); }
template <int N> struct Int { static constexpr int value = N; };

__device__ __forceinline__ uint32_t smem_u32(const void* p) { return (uint32_t)__cvta_generic_to_shared(p); }
__device__ __forceinline__ bool elect() { uint32_t p; asm volatile("{\n.reg .pred p;\nelect.sync _|p, 0xffffffff;\nselp.u32 %0, 1, 0, p;\n}" : "=r"(p)); return p; }
__device__ __forceinline__ void mbar_init(uint32_t bar, uint32_t count) { asm volatile("mbarrier.init.shared::cta.b64 [%0], %1;" ::"r"(bar), "r"(count) : "memory"); }
__device__ __forceinline__ void mbar_expect_tx(uint32_t bar, uint32_t bytes) { asm volatile("mbarrier.arrive.expect_tx.shared::cta.b64 _, [%0], %1;" ::"r"(bar), "r"(bytes) : "memory"); }
__device__ __forceinline__ void mbar_arrive(uint32_t bar) { asm volatile("mbarrier.arrive.shared::cta.b64 _, [%0];" ::"r"(bar) : "memory"); }
__device__ __forceinline__ void mbar_wait(uint32_t bar, uint32_t parity) {
  asm volatile("{\n.reg .pred p;\nWAIT:\nmbarrier.try_wait.parity.shared::cta.b64 p, [%0], %1;\n@!p bra WAIT;\n}" ::"r"(bar), "r"(parity) : "memory");
}
__device__ __forceinline__ void mbar_arrive_cta(uint32_t bar, uint32_t cta) {
  asm volatile("{\n.reg .b32 ra;\nmapa.shared::cluster.u32 ra, %0, %1;\nmbarrier.arrive.shared::cluster.b64 _, [ra];\n}" ::"r"(bar), "r"(cta) : "memory");
}
__device__ __forceinline__ void tma_2d(uint32_t dst, const CUtensorMap* m, uint32_t bar, int c0, int c1) {
  asm volatile("cp.async.bulk.tensor.2d.shared::cluster.global.mbarrier::complete_tx::bytes [%0], [%1, {%3, %4}], [%2];"
               ::"r"(dst), "l"(m), "r"(bar), "r"(c0), "r"(c1) : "memory");
}
__device__ __forceinline__ void tma_3d(uint32_t dst, const CUtensorMap* m, uint32_t bar, int c0, int c1, int c2) {
  asm volatile("cp.async.bulk.tensor.3d.shared::cluster.global.mbarrier::complete_tx::bytes [%0], [%1, {%3, %4, %5}], [%2];"
               ::"r"(dst), "l"(m), "r"(bar), "r"(c0), "r"(c1), "r"(c2) : "memory");
}
__device__ __forceinline__ void tma_3d_mc(uint32_t dst, const CUtensorMap* m, uint32_t bar, int c0, int c1, int c2) {
  asm volatile("cp.async.bulk.tensor.3d.shared::cluster.global.mbarrier::complete_tx::bytes.multicast::cluster [%0], [%1, {%3, %4, %5}], [%2], %6;"
               ::"r"(dst), "l"(m), "r"(bar), "r"(c0), "r"(c1), "r"(c2), "h"((uint16_t)3) : "memory");
}
__device__ __forceinline__ void tma_2d_mc(uint32_t dst, const CUtensorMap* m, uint32_t bar, int c0, int c1) {
  asm volatile("cp.async.bulk.tensor.2d.shared::cluster.global.mbarrier::complete_tx::bytes.multicast::cluster [%0], [%1, {%3, %4}], [%2], %5;"
               ::"r"(dst), "l"(m), "r"(bar), "r"(c0), "r"(c1), "h"((uint16_t)3) : "memory");
}
__device__ __forceinline__ void fence_async() { asm volatile("fence.proxy.async.shared::cta;" ::: "memory"); }
__device__ __forceinline__ void wgmma_fence() { asm volatile("wgmma.fence.sync.aligned;" ::: "memory"); }
__device__ __forceinline__ void wgmma_commit() { asm volatile("wgmma.commit_group.sync.aligned;" ::: "memory"); }
template <int N> __device__ __forceinline__ void wgmma_wait() { asm volatile("wgmma.wait_group.sync.aligned %0;" ::"n"(N) : "memory"); }
__device__ __forceinline__ uint64_t make_desc(uint32_t a16, uint32_t lbo, uint32_t sbo, uint32_t swz) {
  return (uint64_t)(a16 + ((lbo >> 4) << 16)) | ((uint64_t)((sbo >> 4) | (swz << 30)) << 32);
}
__device__ __forceinline__ void bar_sync(int id, int n) { asm volatile("bar.sync %0, %1;" ::"r"(id), "r"(n) : "memory"); }
__device__ __forceinline__ void bar_arrive(int id, int n) { asm volatile("bar.arrive %0, %1;" ::"r"(id), "r"(n) : "memory"); }
__device__ __forceinline__ uint32_t pack_bf16(float lo, float hi) { uint32_t r; asm("cvt.rn.bf16x2.f32 %0, %1, %2;" : "=r"(r) : "f"(hi), "f"(lo)); return r; }
__device__ __forceinline__ uint32_t pack_at(float lo, float hi) { uint32_t r; asm volatile("cvt.rn.bf16x2.f32 %0, %1, %2;" : "=r"(r) : "f"(hi), "f"(lo)); return r; }
__device__ __forceinline__ uint32_t add2(uint32_t a, uint32_t b) { uint32_t r; asm("add.rn.bf16x2 %0, %1, %2;" : "=r"(r) : "r"(a), "r"(b)); return r; }
__device__ __forceinline__ uint32_t sub2(uint32_t a, uint32_t b) { uint32_t r; asm("sub.rn.bf16x2 %0, %1, %2;" : "=r"(r) : "r"(a), "r"(b)); return r; }
__device__ __forceinline__ uint32_t mul2(uint32_t a, uint32_t b) { uint32_t r; asm("mul.rn.bf16x2 %0, %1, %2;" : "=r"(r) : "r"(a), "r"(b)); return r; }
__device__ __forceinline__ float bf_lo(uint32_t w) { return __uint_as_float(w << 16); }
__device__ __forceinline__ float bf_hi(uint32_t w) { return __uint_as_float(w & 0xFFFF0000u); }
__device__ __forceinline__ float bf_round(float v) { return __uint_as_float(pack_bf16(0.f, v)); }
__device__ __forceinline__ float ex2(float v) { float r; asm("ex2.approx.ftz.f32 %0, %1;" : "=f"(r) : "f"(v)); return r; }
__device__ __forceinline__ float rcp(float v) { float r; asm("rcp.approx.ftz.f32 %0, %1;" : "=f"(r) : "f"(v)); return r; }
__device__ __forceinline__ float lg2(float v) { float r; asm("lg2.approx.ftz.f32 %0, %1;" : "=f"(r) : "f"(v)); return r; }
__device__ __forceinline__ float sqr(float v) { float r; asm("sqrt.approx.ftz.f32 %0, %1;" : "=f"(r) : "f"(v)); return r; }
__device__ __forceinline__ float rsq(float v) { float r; asm("rsqrt.approx.ftz.f32 %0, %1;" : "=f"(r) : "f"(v)); return r; }
__device__ __forceinline__ float sigmoid(float v) { return rcp(1.f + ex2(v * -1.4426950408889634f)); }
__device__ __forceinline__ float shx(float v, int o) { return __shfl_xor_sync(0xffffffffu, v, o); }
__device__ __forceinline__ void ldsm4(uint32_t& r0, uint32_t& r1, uint32_t& r2, uint32_t& r3, uint32_t a) { asm volatile("ldmatrix.sync.aligned.m8n8.x4.shared.b16 {%0,%1,%2,%3}, [%4];" : "=r"(r0), "=r"(r1), "=r"(r2), "=r"(r3) : "r"(a) : "memory"); }
__device__ __forceinline__ void ldsm4t(uint32_t& r0, uint32_t& r1, uint32_t& r2, uint32_t& r3, uint32_t a) { asm volatile("ldmatrix.sync.aligned.m8n8.x4.trans.shared.b16 {%0,%1,%2,%3}, [%4];" : "=r"(r0), "=r"(r1), "=r"(r2), "=r"(r3) : "r"(a) : "memory"); }
__device__ __forceinline__ void ldsm2t(uint32_t& r0, uint32_t& r1, uint32_t a) { asm volatile("ldmatrix.sync.aligned.m8n8.x2.trans.shared.b16 {%0,%1}, [%2];" : "=r"(r0), "=r"(r1) : "r"(a) : "memory"); }
__device__ __forceinline__ void stsm4(uint32_t a, uint32_t r0, uint32_t r1, uint32_t r2, uint32_t r3) { asm volatile("stmatrix.sync.aligned.m8n8.x4.shared.b16 [%0], {%1,%2,%3,%4};" ::"r"(a), "r"(r0), "r"(r1), "r"(r2), "r"(r3) : "memory"); }
__device__ __forceinline__ void stsm2(uint32_t a, uint32_t r0, uint32_t r1) { asm volatile("stmatrix.sync.aligned.m8n8.x2.shared.b16 [%0], {%1,%2};" ::"r"(a), "r"(r0), "r"(r1) : "memory"); }
__device__ __forceinline__ uint4 lds16(uint32_t a) { uint4 v; asm volatile("ld.shared.v4.b32 {%0,%1,%2,%3}, [%4];" : "=r"(v.x), "=r"(v.y), "=r"(v.z), "=r"(v.w) : "r"(a) : "memory"); return v; }
__device__ __forceinline__ uint2 lds8(uint32_t a) { uint2 v; asm volatile("ld.shared.v2.b32 {%0,%1}, [%2];" : "=r"(v.x), "=r"(v.y) : "r"(a) : "memory"); return v; }
__device__ __forceinline__ float ldsf(uint32_t a) { float v; asm volatile("ld.shared.f32 %0, [%1];" : "=f"(v) : "r"(a) : "memory"); return v; }
__device__ __forceinline__ void sts16(uint32_t a, uint32_t x, uint32_t y, uint32_t z, uint32_t w) { asm volatile("st.shared.v4.b32 [%0], {%1,%2,%3,%4};" ::"r"(a), "r"(x), "r"(y), "r"(z), "r"(w) : "memory"); }
__device__ __forceinline__ void sts8(uint32_t a, uint32_t x, uint32_t y) { asm volatile("st.shared.v2.b32 [%0], {%1,%2};" ::"r"(a), "r"(x), "r"(y) : "memory"); }
__device__ __forceinline__ void stsf(uint32_t a, float v) { asm volatile("st.shared.f32 [%0], %1;" ::"r"(a), "f"(v) : "memory"); }
__device__ __forceinline__ void mma16(float (&d)[4], uint32_t a0, uint32_t a1, uint32_t a2, uint32_t a3, uint32_t b0, uint32_t b1) {
  asm("mma.sync.aligned.m16n8k16.row.col.f32.bf16.bf16.f32 {%0,%1,%2,%3}, {%4,%5,%6,%7}, {%8,%9}, {%0,%1,%2,%3};"
               : "+f"(d[0]), "+f"(d[1]), "+f"(d[2]), "+f"(d[3]) : "r"(a0), "r"(a1), "r"(a2), "r"(a3), "r"(b0), "r"(b1));
}
__device__ __forceinline__ void mma8(float (&d)[4], uint32_t a0, uint32_t a1, uint32_t b0) {
  asm("mma.sync.aligned.m16n8k8.row.col.f32.bf16.bf16.f32 {%0,%1,%2,%3}, {%4,%5}, {%6}, {%0,%1,%2,%3};"
               : "+f"(d[0]), "+f"(d[1]), "+f"(d[2]), "+f"(d[3]) : "r"(a0), "r"(a1), "r"(b0));
}
__device__ __forceinline__ uint4 ld_msg(const void* p) {
  uint4 v;
  asm volatile("{\n.reg .b128 t;\nld.relaxed.gpu.global.b128 t, [%4];\nmov.b128 {%0, %1, %2, %3}, t;\n}" : "=r"(v.x), "=r"(v.y), "=r"(v.z), "=r"(v.w) : "l"(p) : "memory");
  return v;
}
__device__ __forceinline__ void st_msg(void* p, uint32_t x, uint32_t y, uint32_t z, uint32_t w) {
  asm volatile("{\n.reg .b128 t;\nmov.b128 t, {%1, %2, %3, %4};\nst.relaxed.gpu.global.b128 [%0], t;\n}" ::"l"(p), "r"(x), "r"(y), "r"(z), "r"(w) : "memory");
}
__device__ __forceinline__ void st_msg_if(bool on, void* p, uint32_t x, uint32_t y, uint32_t z, uint32_t w) {
  asm volatile("{\n.reg .b128 t;\n.reg .pred p;\nsetp.ne.u32 p, %5, 0;\nmov.b128 t, {%1, %2, %3, %4};\n@p st.relaxed.gpu.global.b128 [%0], t;\n}"
               ::"l"(p), "r"(x), "r"(y), "r"(z), "r"(w), "r"((uint32_t)on) : "memory");
}
__device__ __forceinline__ void st_word_if(bool on, void* p, uint32_t x) {
  asm volatile("{\n.reg .pred p;\nsetp.ne.u32 p, %2, 0;\n@p st.relaxed.gpu.global.b32 [%0], %1;\n}" ::"l"(p), "r"(x), "r"((uint32_t)on) : "memory");
}
template <int F> __device__ __forceinline__ uint32_t lop3(uint32_t a, uint32_t b, uint32_t c) { uint32_t r; asm("lop3.b32 %0, %1, %2, %3, %4;" : "=r"(r) : "r"(a), "r"(b), "r"(c), "n"(F)); return r; }
__device__ __forceinline__ uint4 ld_words(const void* p) {
  uint4 v;
  asm volatile("ld.relaxed.gpu.global.v4.b32 {%0, %1, %2, %3}, [%4];" : "=r"(v.x), "=r"(v.y), "=r"(v.z), "=r"(v.w) : "l"(p) : "memory");
  return v;
}
__device__ __forceinline__ uint32_t ld_word(const void* p) { uint32_t a; asm volatile("ld.relaxed.gpu.global.b32 %0, [%1];" : "=r"(a) : "l"(p) : "memory"); return a; }
__device__ __forceinline__ void st_word(void* p, uint32_t x) { asm volatile("st.relaxed.gpu.global.b32 [%0], %1;" ::"l"(p), "r"(x) : "memory"); }
__device__ __forceinline__ uint32_t nz(uint32_t w) { uint32_t r; asm("max.u32 %0, %1, 1;" : "=r"(r) : "r"(w)); return r; }
__device__ __forceinline__ bool all(bool p) { return __all_sync(0xffffffffu, p); }
__device__ __forceinline__ uint32_t col_of(uint32_t j, uint32_t c) { return (c < 8 ? 64 * j : 448 + 16 * j) + 8 * c; }
template <class T> __device__ __forceinline__ T* at(T* p, uint32_t i) { T* r; asm("mad.wide.u32 %0, %1, %2, %3;" : "=l"(r) : "r"(i), "n"((int)sizeof(T)), "l"(p)); return r; }
template <int OFF> __device__ __forceinline__ void wait_round(uint4 (&f)[7], const uint4* const (&p)[7], uint32_t tag, int& spin) {
  asm volatile("{\n.reg .pred p;\n.reg .b32 t;\n.reg .b128 v;\nCHECK:\n"
    "lop3.b32 t, %0, %4, %36, 0x7E;\n"
    "lop3.b32 t, t, %8, %36, 0xF6;\n"
    "lop3.b32 t, t, %12, %36, 0xF6;\n"
    "lop3.b32 t, t, %16, %36, 0xF6;\n"
    "lop3.b32 t, t, %20, %36, 0xF6;\n"
    "lop3.b32 t, t, %24, %36, 0xF6;\n"
    "and.b32 t, t, 1;\nsetp.eq.u32 p, t, 0;\nvote.sync.all.pred p, p, 0xffffffff;\n@p bra DONE;\n"
    "ld.relaxed.gpu.global.b128 v, [%29 + %37];\nmov.b128 {%0, %1, %2, %3}, v;\n"
    "ld.relaxed.gpu.global.b128 v, [%30 + %37];\nmov.b128 {%4, %5, %6, %7}, v;\n"
    "ld.relaxed.gpu.global.b128 v, [%31 + %37];\nmov.b128 {%8, %9, %10, %11}, v;\n"
    "ld.relaxed.gpu.global.b128 v, [%32 + %37];\nmov.b128 {%12, %13, %14, %15}, v;\n"
    "ld.relaxed.gpu.global.b128 v, [%33 + %37];\nmov.b128 {%16, %17, %18, %19}, v;\n"
    "ld.relaxed.gpu.global.b128 v, [%34 + %37];\nmov.b128 {%20, %21, %22, %23}, v;\n"
    "ld.relaxed.gpu.global.b128 v, [%35 + %37];\nmov.b128 {%24, %25, %26, %27}, v;\n"
    "add.s32 %28, %28, -1;\nsetp.gt.s32 p, %28, 0;\n@p bra CHECK;\nDONE:\n}"
    : "+r"(f[0].x), "+r"(f[0].y), "+r"(f[0].z), "+r"(f[0].w), "+r"(f[1].x), "+r"(f[1].y), "+r"(f[1].z), "+r"(f[1].w), "+r"(f[2].x), "+r"(f[2].y), "+r"(f[2].z), "+r"(f[2].w), "+r"(f[3].x), "+r"(f[3].y), "+r"(f[3].z), "+r"(f[3].w), "+r"(f[4].x), "+r"(f[4].y), "+r"(f[4].z), "+r"(f[4].w), "+r"(f[5].x), "+r"(f[5].y), "+r"(f[5].z), "+r"(f[5].w), "+r"(f[6].x), "+r"(f[6].y), "+r"(f[6].z), "+r"(f[6].w), "+r"(spin)
    : "l"(p[0]), "l"(p[1]), "l"(p[2]), "l"(p[3]), "l"(p[4]), "l"(p[5]), "l"(p[6]), "r"(tag), "n"(OFF) : "memory");
}
__device__ __forceinline__ void sleep_until(uint32_t t) {
#pragma unroll 1
  while ((int)((uint32_t)clock64() - t) < 0) __nanosleep(100);
}
__device__ __forceinline__ void spin_until(uint32_t t) {
#pragma unroll 1
  while ((int)((uint32_t)clock64() - t) < 0) {}
}

#define X_HDELAY 2500
#define X_PFGAP 600
#define X_GAP0 850
#define X_GAP 850
#define X_GATE 1
#define X_ZCH 1536
#define X_ZKB 3
#define X_ARRK 2
#define X_OGAP 0
#define X_ROLL 1
#define X_HWAIT 200
#define X_KWAIT 200
#define X_YWAIT 300
#define X_SWAIT 250
#define X_HGAP 400
#define X_NCVT 10
#define X_SPLIT 1
#define X_PWG 0
#define X_GKB 5
#define X_PROMO 2
#define X_PROMO2 2
#define X_ZAT 1500
#define X_ZGAP 120
#define X_OL 0
#define X_OWNPF 0
#define X_G1 5
#define X_GGAP 180
#define X_TKB 9
#define X_PERM 0
#define X_WOAT 10
#define X_HN 10
#define X_RWAIT 5500
#define X_GGAP1 200
#define X_TAT 9500
#define X_RWAIT2 14000
#define X_TGAP 150
#define X_WGAP 350
#define X_AWAIT 200
#define X_HALOW 250
#define X_XO 2
#define X_SPEC 0
#define X_HPF 37120
#define X_W0 0
#define X_W2 0
#define X_RDEL 0
#define X_H2 0
#define X_PF1 800
#define X_H0 700
#define X_SN 4
#define X_SL 0
#define X_P2 0
#define X_B2 1
#define X_B1 1
#define X_UPB 2
#define X_GGAP2 250
#define X_DPF 1
#define X_GL 0
#define X_TPF 2

__device__ __forceinline__ void wgmma_n192_ss_ta0_tb1(float (&d)[96], uint64_t da, uint64_t db, int scale_d) {
  asm volatile("{\n.reg .pred p;\nsetp.ne.b32 p, %98, 0;\n"
    "wgmma.mma_async.sync.aligned.m64n192k16.f32.bf16.bf16 "
    "{%0, %1, %2, %3, %4, %5, %6, %7, %8, %9, %10, %11, %12, %13, %14, %15, "
    "%16, %17, %18, %19, %20, %21, %22, %23, %24, %25, %26, %27, %28, %29, %30, %31, "
    "%32, %33, %34, %35, %36, %37, %38, %39, %40, %41, %42, %43, %44, %45, %46, %47, "
    "%48, %49, %50, %51, %52, %53, %54, %55, %56, %57, %58, %59, %60, %61, %62, %63, "
    "%64, %65, %66, %67, %68, %69, %70, %71, %72, %73, %74, %75, %76, %77, %78, %79, "
    "%80, %81, %82, %83, %84, %85, %86, %87, %88, %89, %90, %91, %92, %93, %94, %95}, "
    "%96, %97, p, 1, 1, 0, 1;\n}\n"
    : "+f"(d[0]), "+f"(d[1]), "+f"(d[2]), "+f"(d[3]), "+f"(d[4]), "+f"(d[5]), "+f"(d[6]), "+f"(d[7]), "+f"(d[8]), "+f"(d[9]), "+f"(d[10]), "+f"(d[11]), "+f"(d[12]), "+f"(d[13]), "+f"(d[14]), "+f"(d[15]), "+f"(d[16]), "+f"(d[17]), "+f"(d[18]), "+f"(d[19]), "+f"(d[20]), "+f"(d[21]), "+f"(d[22]), "+f"(d[23]), "+f"(d[24]), "+f"(d[25]), "+f"(d[26]), "+f"(d[27]), "+f"(d[28]), "+f"(d[29]), "+f"(d[30]), "+f"(d[31]), "+f"(d[32]), "+f"(d[33]), "+f"(d[34]), "+f"(d[35]), "+f"(d[36]), "+f"(d[37]), "+f"(d[38]), "+f"(d[39]), "+f"(d[40]), "+f"(d[41]), "+f"(d[42]), "+f"(d[43]), "+f"(d[44]), "+f"(d[45]), "+f"(d[46]), "+f"(d[47]), "+f"(d[48]), "+f"(d[49]), "+f"(d[50]), "+f"(d[51]), "+f"(d[52]), "+f"(d[53]), "+f"(d[54]), "+f"(d[55]), "+f"(d[56]), "+f"(d[57]), "+f"(d[58]), "+f"(d[59]), "+f"(d[60]), "+f"(d[61]), "+f"(d[62]), "+f"(d[63]), "+f"(d[64]), "+f"(d[65]), "+f"(d[66]), "+f"(d[67]), "+f"(d[68]), "+f"(d[69]), "+f"(d[70]), "+f"(d[71]), "+f"(d[72]), "+f"(d[73]), "+f"(d[74]), "+f"(d[75]), "+f"(d[76]), "+f"(d[77]), "+f"(d[78]), "+f"(d[79]), "+f"(d[80]), "+f"(d[81]), "+f"(d[82]), "+f"(d[83]), "+f"(d[84]), "+f"(d[85]), "+f"(d[86]), "+f"(d[87]), "+f"(d[88]), "+f"(d[89]), "+f"(d[90]), "+f"(d[91]), "+f"(d[92]), "+f"(d[93]), "+f"(d[94]), "+f"(d[95])
    : "l"(da), "l"(db), "r"(scale_d));
}

__device__ __forceinline__ void wgmma_n48_ss_ta0_tb1(float (&d)[24], uint64_t da, uint64_t db, int scale_d) {
  asm volatile("{\n.reg .pred p;\nsetp.ne.b32 p, %26, 0;\n"
    "wgmma.mma_async.sync.aligned.m64n48k16.f32.bf16.bf16 "
    "{%0, %1, %2, %3, %4, %5, %6, %7, %8, %9, %10, %11, %12, %13, %14, %15, "
    "%16, %17, %18, %19, %20, %21, %22, %23}, "
    "%24, %25, p, 1, 1, 0, 1;\n}\n"
    : "+f"(d[0]), "+f"(d[1]), "+f"(d[2]), "+f"(d[3]), "+f"(d[4]), "+f"(d[5]), "+f"(d[6]), "+f"(d[7]), "+f"(d[8]), "+f"(d[9]), "+f"(d[10]), "+f"(d[11]), "+f"(d[12]), "+f"(d[13]), "+f"(d[14]), "+f"(d[15]), "+f"(d[16]), "+f"(d[17]), "+f"(d[18]), "+f"(d[19]), "+f"(d[20]), "+f"(d[21]), "+f"(d[22]), "+f"(d[23])
    : "l"(da), "l"(db), "r"(scale_d));
}

__device__ __forceinline__ void wgmma_n192_rs_ta0_tb1(float (&d)[96], uint32_t a0, uint32_t a1, uint32_t a2, uint32_t a3, uint64_t db, int scale_d) {
  asm volatile("{\n.reg .pred p;\nsetp.ne.b32 p, %101, 0;\n"
    "wgmma.mma_async.sync.aligned.m64n192k16.f32.bf16.bf16 "
    "{%0, %1, %2, %3, %4, %5, %6, %7, %8, %9, %10, %11, %12, %13, %14, %15, "
    "%16, %17, %18, %19, %20, %21, %22, %23, %24, %25, %26, %27, %28, %29, %30, %31, "
    "%32, %33, %34, %35, %36, %37, %38, %39, %40, %41, %42, %43, %44, %45, %46, %47, "
    "%48, %49, %50, %51, %52, %53, %54, %55, %56, %57, %58, %59, %60, %61, %62, %63, "
    "%64, %65, %66, %67, %68, %69, %70, %71, %72, %73, %74, %75, %76, %77, %78, %79, "
    "%80, %81, %82, %83, %84, %85, %86, %87, %88, %89, %90, %91, %92, %93, %94, %95}, "
    "{%96, %97, %98, %99}, %100, p, 1, 1, 1;\n}\n"
    : "+f"(d[0]), "+f"(d[1]), "+f"(d[2]), "+f"(d[3]), "+f"(d[4]), "+f"(d[5]), "+f"(d[6]), "+f"(d[7]), "+f"(d[8]), "+f"(d[9]), "+f"(d[10]), "+f"(d[11]), "+f"(d[12]), "+f"(d[13]), "+f"(d[14]), "+f"(d[15]), "+f"(d[16]), "+f"(d[17]), "+f"(d[18]), "+f"(d[19]), "+f"(d[20]), "+f"(d[21]), "+f"(d[22]), "+f"(d[23]), "+f"(d[24]), "+f"(d[25]), "+f"(d[26]), "+f"(d[27]), "+f"(d[28]), "+f"(d[29]), "+f"(d[30]), "+f"(d[31]), "+f"(d[32]), "+f"(d[33]), "+f"(d[34]), "+f"(d[35]), "+f"(d[36]), "+f"(d[37]), "+f"(d[38]), "+f"(d[39]), "+f"(d[40]), "+f"(d[41]), "+f"(d[42]), "+f"(d[43]), "+f"(d[44]), "+f"(d[45]), "+f"(d[46]), "+f"(d[47]), "+f"(d[48]), "+f"(d[49]), "+f"(d[50]), "+f"(d[51]), "+f"(d[52]), "+f"(d[53]), "+f"(d[54]), "+f"(d[55]), "+f"(d[56]), "+f"(d[57]), "+f"(d[58]), "+f"(d[59]), "+f"(d[60]), "+f"(d[61]), "+f"(d[62]), "+f"(d[63]), "+f"(d[64]), "+f"(d[65]), "+f"(d[66]), "+f"(d[67]), "+f"(d[68]), "+f"(d[69]), "+f"(d[70]), "+f"(d[71]), "+f"(d[72]), "+f"(d[73]), "+f"(d[74]), "+f"(d[75]), "+f"(d[76]), "+f"(d[77]), "+f"(d[78]), "+f"(d[79]), "+f"(d[80]), "+f"(d[81]), "+f"(d[82]), "+f"(d[83]), "+f"(d[84]), "+f"(d[85]), "+f"(d[86]), "+f"(d[87]), "+f"(d[88]), "+f"(d[89]), "+f"(d[90]), "+f"(d[91]), "+f"(d[92]), "+f"(d[93]), "+f"(d[94]), "+f"(d[95])
    : "r"(a0), "r"(a1), "r"(a2), "r"(a3), "l"(db), "r"(scale_d));
}

__device__ __forceinline__ void wgmma_n48_rs_ta0_tb1(float (&d)[24], uint32_t a0, uint32_t a1, uint32_t a2, uint32_t a3, uint64_t db, int scale_d) {
  asm volatile("{\n.reg .pred p;\nsetp.ne.b32 p, %29, 0;\n"
    "wgmma.mma_async.sync.aligned.m64n48k16.f32.bf16.bf16 "
    "{%0, %1, %2, %3, %4, %5, %6, %7, %8, %9, %10, %11, %12, %13, %14, %15, "
    "%16, %17, %18, %19, %20, %21, %22, %23}, "
    "{%24, %25, %26, %27}, %28, p, 1, 1, 1;\n}\n"
    : "+f"(d[0]), "+f"(d[1]), "+f"(d[2]), "+f"(d[3]), "+f"(d[4]), "+f"(d[5]), "+f"(d[6]), "+f"(d[7]), "+f"(d[8]), "+f"(d[9]), "+f"(d[10]), "+f"(d[11]), "+f"(d[12]), "+f"(d[13]), "+f"(d[14]), "+f"(d[15]), "+f"(d[16]), "+f"(d[17]), "+f"(d[18]), "+f"(d[19]), "+f"(d[20]), "+f"(d[21]), "+f"(d[22]), "+f"(d[23])
    : "r"(a0), "r"(a1), "r"(a2), "r"(a3), "l"(db), "r"(scale_d));
}

__device__ __forceinline__ void wgmma_n80_rs_ta0_tb1(float (&d)[40], uint32_t a0, uint32_t a1, uint32_t a2, uint32_t a3, uint64_t db, int scale_d) {
  asm volatile("{\n.reg .pred p;\nsetp.ne.b32 p, %45, 0;\n"
    "wgmma.mma_async.sync.aligned.m64n80k16.f32.bf16.bf16 "
    "{%0, %1, %2, %3, %4, %5, %6, %7, %8, %9, %10, %11, %12, %13, %14, %15, "
    "%16, %17, %18, %19, %20, %21, %22, %23, %24, %25, %26, %27, %28, %29, %30, %31, "
    "%32, %33, %34, %35, %36, %37, %38, %39}, "
    "{%40, %41, %42, %43}, %44, p, 1, 1, 1;\n}\n"
    : "+f"(d[0]), "+f"(d[1]), "+f"(d[2]), "+f"(d[3]), "+f"(d[4]), "+f"(d[5]), "+f"(d[6]), "+f"(d[7]), "+f"(d[8]), "+f"(d[9]), "+f"(d[10]), "+f"(d[11]), "+f"(d[12]), "+f"(d[13]), "+f"(d[14]), "+f"(d[15]), "+f"(d[16]), "+f"(d[17]), "+f"(d[18]), "+f"(d[19]), "+f"(d[20]), "+f"(d[21]), "+f"(d[22]), "+f"(d[23]), "+f"(d[24]), "+f"(d[25]), "+f"(d[26]), "+f"(d[27]), "+f"(d[28]), "+f"(d[29]), "+f"(d[30]), "+f"(d[31]), "+f"(d[32]), "+f"(d[33]), "+f"(d[34]), "+f"(d[35]), "+f"(d[36]), "+f"(d[37]), "+f"(d[38]), "+f"(d[39])
    : "r"(a0), "r"(a1), "r"(a2), "r"(a3), "l"(db), "r"(scale_d));
}

template <bool kUseSmid>
__global__ void __cluster_dims__(2, 1, 1) __launch_bounds__(384, 1) fused_block_kernel(const uint8_t* __restrict__ gx, const uint8_t* __restrict__ gw, const __grid_constant__ Params P) {
  extern __shared__ __align__(1024) uint8_t smem_raw[];
  const uint32_t c_entry = (uint32_t)clock64();
  const uint32_t tid = threadIdx.x;
  uint32_t id = blockIdx.x;
  if (kUseSmid) asm volatile("mov.u32 %0, %%smid;" : "=r"(id));
  if (tid < 16) {
    const uint32_t i = (id & 127) * 8 + (tid & 7);
    asm volatile("prefetch.global.L2 [%0];" ::"l"((tid < 8 ? gx : gw) + (tid < 8 ? (i + (i & ~127u) + 128) * 10 : i) * 128));
  }
  const uint32_t sw = __shfl_sync(0xffffffffu, smem_u32(smem_raw) + (id << 12) + (tid >> 5), 0);
  const uint32_t sb = kUseSmid ? sw & 0xFF000400u : smem_u32(smem_raw), warp = sw & 31;
  if (kUseSmid) id = (sw >> 12) & 255;
#define BAR(i) (sb + kBars + 8 * (i))
  if (warp >= 8) {
    if (elect()) {
      const uint32_t cnt = (0x1381u >> (4 * warp - 32)) & 15;
#pragma unroll
      for (int i = 0; i < 4; i++) mbar_init(BAR(4 * (warp - 8) + i), cnt);
      asm volatile("fence.mbarrier_init.release.cluster;" ::: "memory");
    }
    asm volatile("barrier.cluster.arrive.relaxed.aligned;" ::: "memory");
  } else {
    asm volatile("barrier.cluster.arrive.relaxed.aligned;" ::: "memory");
    if (warp == 1 && elect()) {
#pragma unroll
      for (int i = 0; i < 3; i++) asm volatile("prefetch.tensormap [%0];" ::"l"(&P.mx + i) : "memory");
    }
  }
  if (warp != 8) asm volatile("barrier.cluster.wait.aligned;" ::: "memory");
  const uint32_t lane = __shfl_sync(0xffffffffu, tid & 31, tid & 31);
  const uint32_t tp = id >> 1, par = kUseSmid ? sw >> 24 : id & 1;
  uint32_t beta = tp & 7, idx = tp >> 3;
  if (tp >= 32) { const uint32_t u = tp - 32, d = (u * 37) >> 8, r = u - 7 * d; beta = d < 4 ? 1 + r : 0; idx = d < 4 ? 4 + d : 2 + r; }
  if ((tp >> 1) == 30) {
    const uint32_t h = (id - 120) * 384 + tid;
    uint4* z = P.scr + offsetof(Scratch, halo) / 16 + h;
    spin_until(c_entry + X_ZAT);
#pragma unroll 1
    for (uint32_t n = 0; n < kReset; n++) {
      z[n * 1536] = make_uint4(0, 0, 0, 0);
      if (n == kReset1 - 1 || n == kReset2 - 1 || n == kReset - 1) {
        __syncthreads();
        if (tid == 0) asm volatile("red.release.gpu.global.add.u32 [%0], 1;" ::"l"(P.count + (n + 1) / 12 * 32) : "memory");
      }
      if (n == kReset1 - 1 || n == kReset2 - 1) {
#pragma unroll 1
        for (uint32_t l = n == kReset1 - 1 ? h : 6400 + h; l < (n == kReset1 - 1 ? 6400 : X_HPF); l += 1536)
          asm volatile("prefetch.global.L2 [%0];" ::"l"((l < 6400 ? P.wo : l < 21760 ? P.wup - 6400 * 128 : P.wdown - 21760 * 128) + l * 128));
      }
    }
    return;
  }
  const uint32_t rb = (beta & 3) * 2 + (idx >> 2), hg = (beta & 4) + (idx & 3);
  const uint32_t tile = 2 * rb + par, cta = tile * 8 + hg;
#define UNIT(field, i) (at(P.scr, i) + offsetof(Scratch, field) / 16)
#define WORD(field, i) (at(reinterpret_cast<uint32_t*>(P.scr), i) + offsetof(Scratch, field) / 4)

  const uint32_t g = lane >> 2, q = lane & 3, m = lane >> 3, l7 = lane & 7;
  int spin = kSpin;

  if (warp >= 8) {
    asm volatile("setmaxnreg.dec.sync.aligned.u32 56;");
    auto permute = [&]() {
      mbar_wait(BAR(B_TAIL), 0);
      PROF(31);
      const uint32_t a = sb + kWoTail + (X_P2 ? (warp & 1) * 10240 : 0) + lane * 16, x = (2 * (hg & 3) ^ m) << 4;
#pragma unroll 1
      for (int i = 0; i < (X_P2 ? 10240 : 20480); i += 2048) {
        uint4 v[4];
#pragma unroll
        for (int e = 0; e < 4; e++) v[e] = lds16(a + i + e * 512);
        __syncwarp();
#pragma unroll
        for (int e = 0; e < 4; e++) sts16((a ^ x ^ (e & 1) * 64) + i + e * 512, v[e].x, v[e].y, v[e].z, v[e].w);
      }
      fence_async();
      __syncwarp();
      PROF(21);
    };
    auto wait_reset = [&](int i, uint32_t e) {
      unsigned c;
#pragma unroll 1
      do {
        asm volatile("ld.acquire.gpu.global.u32 %0, [%1];" : "=r"(c) : "l"(P.count + i) : "memory");
      } while (c != 4 * e && --spin > 0);
    };
    if (warp == 8) {
      asm volatile("barrier.cluster.wait.aligned;" ::: "memory");
      PROF(1);
#pragma unroll 1
      for (uint32_t kb = 0; kb < 10; kb++) {
        if (kb) spin_until(c_entry + X_GAP0 + kb * X_GAP);
        if (kb >= 4) mbar_wait(BAR(B_EMPTY + (kb & 3)), kb >> 3);
        if (elect()) {
          const uint32_t s = sb + ((kb + 2) & 3) * kStage;
#pragma unroll 1
          for (uint32_t h = 0; h < 2; h++) {
            const uint32_t fb = BAR((h ? B_FULL : B_HALF) + (kb & 3)), ks = 2 * h + par;
            if (h && kb == 0) spin_until(c_entry + X_H0);
            mbar_expect_tx(fb, kStage / 2);
            tma_3d_mc(s + 16384 + ks * 6144, &P.mw64, fb, 80 * hg, kb * 64 + 16 * ks, 0);
            tma_3d_mc(s + 40960 + ks * 1536, &P.mw16, fb, 80 * hg + 64, kb * 64 + 16 * ks, 0);
            tma_2d(s + 8192 - h * 8192, &P.mx, fb, par * 640 + kb * 64, rb * 128 + 64 - h * 64);
          }
        }
        if (kb == 0) spin_until(c_entry + X_PF1);
        if (kb < 9 && lane < 31) asm volatile("prefetch.global.L2 [%0];" ::"l"((lane < 16 ? gx : gw) + (lane < 16 ? (cta * 16 + lane) * 10 + kb + 1 : cta * 15 + lane + kb * 1920 + 1904) * 128));
      }
      const uint32_t fc = 32 * (rb * 8 + hg);
      const bool ffn = cta < 96 && elect();
      if (ffn) {
        mbar_expect_tx(BAR(B_FFN), 61440);
        asm volatile("mbarrier.arrive.shared::cta.b64 _, [%0], 2;" ::"r"(BAR(B_FFN)) : "memory");
      }
#pragma unroll 1
      for (uint32_t n = 0; n < 5; n++) {
        mbar_wait(BAR(B_EMPTY + 2 + (n >= 2)), 1);
        const uint32_t t = (uint32_t)clock64(), i = 2 * n + par;
        if (n < 4 && elect()) tma_2d_mc(sb + kWo + i * 10240, &P.mwo, BAR(B_WO), 64 * hg, 80 * (hg ^ i));
        spin_until(t + X_WGAP);
        if (cta < 96 && elect()) tma_2d(sb + kGate + n * 4096, &P.mgate, BAR(B_FFN), fc, n < 4 ? 256 * par + 64 * n : 512 + 64 * par);
        spin_until(t + X_WGAP + X_GGAP);
      }
      if (ffn) mbar_expect_tx(BAR(B_FULL + 2), 1024);
      PROF(20);
      bar_sync(NB_OL, 288);
      if (cta >= 96) return;
      uint32_t t = (uint32_t)clock64() + X_W2;
#pragma unroll 1
      for (uint32_t n = 0; n < 5; n++) {
        spin_until(t);
        if (elect()) tma_2d(sb + kUp + n * 4096, &P.mup, BAR(B_FFN), fc, n < 4 ? 256 * par + 64 * n : 512 + 64 * par);
        spin_until(t + X_GGAP2);
        if (elect()) tma_3d(sb + kDown + n * 4096, &P.mdown, BAR(B_FFN), 0, fc + 16 * par, 2 * n);
        t += (2 + X_GL) * X_GGAP2;
      }
      PROF(60);
      return;
    }
    if (warp == 11) {
      if (elect()) {
        mbar_expect_tx(BAR(B_TAIL), 20480);
        asm volatile("mbarrier.arrive.shared::cta.b64 _, [%0], 2;" ::"r"(BAR(B_TAIL)) : "memory");
      }
      const uint32_t e = ld_word(P.count) + 1;
      sleep_until(c_entry + X_RWAIT);
      if (elect()) {
#pragma unroll 1
        for (int i = 0; i < 5; i++) asm volatile("prefetch.tensormap [%0];" ::"l"(&P.mwo + i) : "memory");
      }
      __syncwarp();
      wait_reset(32, e);
      sts8(sb + kMisc, e, e & 1);
      if (elect()) mbar_arrive(BAR(B_AUX));
      PROF(22);
      bar_arrive(NB_GRID, 96);
      sleep_until(c_entry + X_TAT);
      if (elect()) {
#pragma unroll 1
        for (uint32_t n = 0; n < 4; n++) {
          const uint32_t t = (uint32_t)clock64() + X_TGAP;
          tma_3d_mc(sb + kWoTail + par * 10240 + n * 2560, &P.mtail, BAR(B_TAIL), 512 + 16 * hg, (hg & 4) ^ (4 * par), 20 * n);
          spin_until(t);
        }
      }
      __syncwarp();
      permute();
      if (elect()) asm volatile("mbarrier.arrive.shared::cta.b64 _, [%0], 2;" ::"r"(BAR(B_WO)) : "memory");
      sleep_until(c_entry + X_RWAIT2);
      wait_reset(64, e);
      PROF(30);
      if (elect()) asm volatile("mbarrier.arrive.shared::cta.b64 _, [%0], 3;" ::"r"(BAR(B_TAIL)) : "memory");
    } else {
      const bool cw = warp == 10;
      const uint32_t u = min(tile, 14u);
      uint32_t o0 = (16 * hg + (lane & 15)) * 128 + (((m >> 1) ^ l7) << 4), o1 = o0 ^ 32, o2 = o0 ^ 64, o3 = o0 ^ 96;
      if (cw) {
        const uint32_t k = 8 * (m >> 1) + l7, st = u < 12 ? 6144 : 1536;
        o0 = u < 12 ? 16384 + (u >> 2) * 2048 + k * 128 + (((2 * (u & 3) + (m & 1)) ^ l7) << 4) : 34816 + u * 512 + k * 32 + (((m & 1) ^ (l7 >> 2)) << 4);
        o1 = o0 + st; o2 = o1 + st; o3 = o2 + st;
      }
      const uint32_t side = sb + kUpSide + cw * 4096;
      const uint32_t e0 = cw ? (8 * (m >> 1) + l7) * 32 + (((m & 1) ^ (l7 >> 2)) << 4) : o0 - hg * 2048, ex = cw ? 512 : 32;
      float s0 = 0.f, s1 = 0.f, q0 = 0.f, q1 = 0.f;
#pragma unroll 1
      for (uint32_t n = 0; n < 10; n++) {
        const bool sd = n - X_SN < 2;
        const uint32_t kb = n < X_SN ? n : n - 2;
        if (n == 9) bar_sync(NB_GRID, 96);
        if (sd) {
          asm volatile("cp.async.wait_all;" ::: "memory");
          __syncwarp();
        } else {
          mbar_wait(BAR(B_HALF + (kb & 3)), kb >> 2);
          mbar_wait(BAR(B_FULL + (kb & 3)), kb >> 2);
          if (warp == 9) PROF2(47, kb);
        }
        if (n == X_SL) {
          const uint8_t* src = cw ? gw + (512 + (lane >> 1)) * 3840 + (u < 12 ? (u >> 2) * 1280 + (u & 3) * 32 : u * 1280 - 12 * 1280 + 128) + 160 * hg + (lane & 1) * 16
                                  : gx + (256 * rb + par + 32 * hg + 2 * (lane >> 4)) * 1280 + 1024 + (lane & 15) * 16;
#pragma unroll 1
          for (uint32_t i = 0; i < 8; i++) {
            const uint32_t row = 2 * i + (lane >> 4);
            const uint32_t dst = cw ? i * 512 + ((lane ^ (lane >> 3 & 1)) << 4) : (lane & 8) * 256 + row * 128 + ((l7 ^ (row & 7)) << 4);
            asm volatile("cp.async.cg.shared.global [%0], [%1], 16;" ::"r"(side + dst), "l"(src + i * (cw ? 16 * 3840 : 5120)) : "memory");
          }
        }
        const uint32_t s = sd ? side + (n - X_SN) * 2048 : sb + ((kb + 2) & 3) * kStage;
        const uint32_t a0 = s + (sd ? e0 : o0), a1 = s + (sd ? e0 ^ ex : o1), a2 = s + (sd ? e0 ^ 2 * ex : o2), a3 = s + (sd ? e0 ^ 3 * ex : o3);
        uint32_t r[16];
        if (cw) { ldsm4t(r[0], r[1], r[2], r[3], a0); ldsm4t(r[4], r[5], r[6], r[7], a1); ldsm4t(r[8], r[9], r[10], r[11], a2); ldsm4t(r[12], r[13], r[14], r[15], a3); }
        else { ldsm4(r[0], r[1], r[2], r[3], a0); ldsm4(r[4], r[5], r[6], r[7], a1); ldsm4(r[8], r[9], r[10], r[11], a2); ldsm4(r[12], r[13], r[14], r[15], a3); }
#pragma unroll
        for (int i = 0; i < 16; i += 2) {
          const float a = bf_lo(r[i]), b = bf_hi(r[i]), c = bf_lo(r[i + 1]), d = bf_hi(r[i + 1]);
          s0 += a; s0 += b; q0 = fmaf(a, a, q0); q0 = fmaf(b, b, q0);
          s1 += c; s1 += d; q1 = fmaf(c, c, q1); q1 = fmaf(d, d, q1);
        }
        if (lane < 2 && !sd) mbar_arrive_cta(BAR(B_EMPTY + (kb & 3)) + (__float_as_uint(q0) >> 31), lane);
      }
      PROF2(23, cw);
      s0 = (q & 1 ? s1 : s0) + shx(q & 1 ? s0 : s1, 1); q0 = (q & 1 ? q1 : q0) + shx(q & 1 ? q0 : q1, 1);
      s0 += shx(s0, 2); q0 += shx(q0, 2);
      s0 *= cw ? 1.f : -1.f / 640;
      uint32_t w = pack_bf16(s0, s0 - bf_round(s0));
      const float r = bf_round(sqr(bf_round(bf_round(fmaxf(fmaf(q0, 1.f / 640, -s0 * s0), 0.f)) + 1e-5f)));
      if (cw) asm volatile("movmatrix.sync.aligned.m8n8.trans.b16 %0, %0;" : "+r"(w));
      else if (q & 2) w = __float_as_uint(r);
      const uint32_t src = cw ? (uint32_t)(offsetof(Scratch, cs) / 16) + hg * 64 : (uint32_t)(offsetof(Scratch, stat1) / 16) - 8 + (par * 8 + rb) * 64;
      st_word_if(!cw || lane < 16, WORD(obuf, 4 * src + (cw ? 16 * u : 32 + 32 * hg) + lane), nz(w));
      PROF2(57, cw);
      {
        const uint32_t i0 = (cw || rb) ? lane : max(lane, 8u), i1 = min(lane + 32, cw ? 59u : 63u), i2 = cw ? 59 : 64 + l7;
        uint4 v0, v1, v2;
        spin_until((uint32_t)clock64() + X_AWAIT);
#pragma unroll 1
        do {
          v0 = ld_words(UNIT(obuf, src + i0)); v1 = ld_words(UNIT(obuf, src + i1)); v2 = ld_words(UNIT(obuf, src + i2));
        } while (!all(min(min(min(min(v0.x, v0.y), min(v0.z, v0.w)), min(min(v1.x, v1.y), min(v1.z, v1.w))), min(min(v2.x, v2.y), min(v2.z, v2.w)))) && --spin > 0);
        const uint32_t d = sb + (cw ? kBext : kStat);
        sts16(d + lane * 16, v0.x, v0.y, v0.z, v0.w); sts16(d + 512 + lane * 16, v1.x, v1.y, v1.z, v1.w); sts16(d + 1024 + l7 * 16, v2.x, v2.y, v2.z, v2.w);
      }
      fence_async();
      __syncwarp();
      if (elect()) mbar_arrive(BAR(B_AUX));
      PROF2(25, cw);
      mbar_wait(BAR(B_HALF + 1), 0);
      if (lane < 4) mbar_arrive_cta(BAR(B_EMPTY + (lane >> 1)), lane & 1);
      auto note = [&](int i, uint32_t wait) {
        uint32_t* const hp = WORD(hint, tile * 32 + l7) + 512 * i;
        st_word_if(lane == hg, hp, 1);
        spin_until((uint32_t)clock64() + wait);
#pragma unroll 1
        while (!all(ld_word(hp)) && --spin > 0) {}
      };
      if (!cw) {
        uint4 v[5];
        mbar_wait(BAR(B_EMPTY + 3), 1);
        bar_sync(NB_RED, 64);
        spin_until((uint32_t)clock64() + X_HALOW);
#pragma unroll 1
        do {
          PROF(5);
#pragma unroll
          for (int i = 0; i < 5; i++) v[i] = ld_msg(UNIT(halo0, cta * 160 + lane) + 32 * i);
        } while (!all(min(min(v[0].x, v[1].x), min(min(v[2].x, v[3].x), v[4].x))) && rb && --spin > 0);
        sts16(sb + kKst + lane * 16, v[0].x, v[0].y, v[0].z, v[0].w);
        sts16(sb + kKst + 512 + lane * 16, v[1].x, v[1].y, v[1].z, v[1].w);
        sts8(sb + kKst + 1024 + lane * 8, v[2].x, v[2].y);
        const uint32_t a = sb + kVst + l7 * kPitch + m * 16;
        stsm4(a, v[3].x, v[3].y, v[3].z, v[3].w);
        stsm4(a + 64, v[4].x, v[4].y, v[4].z, v[4].w);
        stsm2(a + 128, v[2].z, v[2].w);
        bar_arrive(NB_KV, 64);
        PROF(27);
        mbar_wait(BAR(B_EMPTY + 1), 0);
        bar_sync(NB_KEY, 288);
        const uint32_t tag = __float_as_uint(ldsf(sb + kMisc + 4));
        uint32_t best = __reduce_max_sync(0xffffffffu, __float_as_uint(ldsf(sb + kMisc + 16 + l7 * 4))), prev, k;
        st_word_if(lane + hg == 0, WORD(keys, tile), best);
        PROF(13);
        wait_reset(96, __float_as_uint(ldsf(sb + kMisc)));
        auto load_row = [&]() {
          const uint32_t tok = ~best;
          const uint4* p = UNIT(cand, ((tok >> 4 & 0x70) + (tok & 1) * 8 + (tok >> 5 & 7)) * 96 + par * 48 + (g & 3) * 12 + q);
#pragma unroll
          for (int i = 0; i < 3; i++) v[i] = ld_msg(p + 4 * i);
        };
#pragma unroll 1
        do { k = ld_word(WORD(keys, lane & 15)); } while (!all(k) && --spin > 0);
        best = __reduce_max_sync(0xffffffffu, k);
        PROF(14);
        load_row();
#pragma unroll 1
        while (!all(!(lop3<0xF6>(lop3<0x7E>(v[0].x, v[1].x, tag), v[2].w, tag) & 1)) && --spin > 0) load_row();
        v[0].x = __byte_perm(v[0].x, v[2].z, 0x3254); v[1].x = __byte_perm(v[1].x, v[2].z, 0x3276);
#pragma unroll
        for (int i = 0; i < 3; i++) sts16(sb + kSel + lane * 48 + 16 * i, v[i].x, v[i].y, v[i].z, v[i].w);
        stsf(sb + kMisc + 8, __uint_as_float(best));
        st_word_if(lane + cta == 0, P.count, __float_as_uint(ldsf(sb + kMisc)));
        bar_arrive(NB_KEY + 1, 288);
        PROF(15);
        return;
      }
      mbar_wait(BAR(B_EMPTY + 1), 0);
      note(0, X_HWAIT);
      PROF(29);
      if (elect()) mbar_expect_tx(BAR(B_WO), 81920);
    }
    bar_sync(warp & 1 ? 0 : NB_GRID, 160);
#pragma unroll 1
    for (uint32_t n = 0; n < 20; n++) {
      const uint32_t w = 4 * (warp & 1) + (n & 3), row = n < 16 ? (n & 12) + m : lane >> 1, ch = n < 16 ? l7 : 8 + (lane & 1);
      const uint32_t ao = sb + kOutSt + w * (16 * kPitch);
      const uint4 v = lds16(ao + row * kPitch + ch * 16);
      if (row != __float_as_uint(ldsf(ao + 160))) *at(reinterpret_cast<uint4*>(P.out), (256 * rb + par + 32 * w + 2 * row) * 80 + (n < 16 ? 8 * hg : 56 + 2 * hg) + ch) = v;
    }
    PROF(59);
  } else {
    asm volatile("setmaxnreg.inc.sync.aligned.u32 224;");
    const uint32_t wg = warp >> 2;
    const uint32_t s16 = kUseSmid ? 64u : (sb & 0x3FFFF) >> 4;
    const bool gt0 = 2 * q > g, gt1 = 2 * q + 1 > g;
    const bool rel = lane + 8 * (warp & 3) < 2;
    uint32_t w[10];
#pragma unroll
    for (int c = 0; c < 10; c++) asm volatile("ld.global.nc.b32 %0, [%1];" : "=r"(w[c]) : "l"(at(P.wr, (c < 8 ? 32 * hg : 8 * hg) + q) + (c < 8 ? 4 * c : 224 + 4 * c)));
    float acc1[96], acc2[24];
    const uint32_t ax = sb + (16 * warp + (lane & 15)) * 128 + (((lane >> 4) ^ l7) << 4);
    uint32_t xr[10][2];
#pragma unroll 1
    for (uint32_t kb = 0;; kb++) {
      const uint32_t so = ((kb + 2) & 3) * kStage;
      if (wg) mbar_wait(BAR(B_HALF + (kb & 3)), (kb >> 2) & 1);
      if (warp == 4) PROF2(32, kb);
      if (kb < 9) {
        wgmma_wait<0>();
        if (rel && kb) mbar_arrive_cta(BAR(B_EMPTY + ((kb - 1) & 3)), lane);
        if (wg == 0 || kb) bar_sync(NB_TURN + wg, 256);
      }
      wgmma_fence();
      const uint32_t da = s16 + (so >> 4) + wg * 512, db = s16 + (so >> 4) + 1024;
#pragma unroll
      for (int k = 0; k < 4; k++) {
        if (k == 2 && wg) mbar_wait(BAR(B_FULL + (kb & 3)), (kb >> 2) & 1);
        wgmma_n192_ss_ta0_tb1(acc1, make_desc(da + 2 * k, 16, 1024, 1), make_desc(db + 384 * k, 2048, 1024, 1), (kb | k) != 0);
        wgmma_n48_ss_ta0_tb1(acc2, make_desc(da + 2 * k, 16, 1024, 1), make_desc(db + 1536 + 96 * k, 512, 256, 3), (kb | k) != 0);
        if (k == X_ARRK && kb < 8) bar_arrive(NB_TURN + 1 - wg, 256);
      }
      wgmma_commit();
      if (kb == hg) {
#pragma unroll
        for (int i = 0; i < 4; i++) ldsm4(xr[2 * i][0], xr[2 * i][1], xr[2 * i + 1][0], xr[2 * i + 1][1], (ax + so) ^ (32 * i));
        bar_sync(NB_WG + wg, 128);
      }
      if (kb == 9) break;
    }
    uint32_t tag;
    float fs[4], lb[4];
    uint32_t ak = sb + kKst + warp * 1280 + lane * 16, ak1 = ak + 1024 - lane * 8;
    const uint32_t av = sb + kVst + (16 * warp + l7) * kPitch;
    uint32_t ac = av + m * 16, ae = av + ((m + 1) >> 1) * (8 * kPitch), bandm = (gt0 ? 0xFFFFu : 0u) | (gt1 ? 0xFFFF0000u : 0u);
    const uint32_t tw = tile * 8 + warp, oo = tw * 1280 + hg * 32 + lane;
    uint4* op = UNIT(obuf, oo);
    float acc[40];
    uint32_t sg[3];
    {
      ldsm4(xr[8][0], xr[8][1], xr[9][0], xr[9][1], (ax + (2 + (hg >> 2)) * kStage) ^ (32 * (hg & 3)));
      mbar_wait(BAR(B_AUX), 0);
      const uint32_t sa = sb + kStat + 128 + warp * 128;
      const uint4 st = lds16(sa + g * 16);
      const uint32_t m0 = q ? xr[8][0] & st.z & 1u : st.x, m1 = q ? 0u : st.y;
      const uint32_t a0 = __byte_perm(m0, 0, 0x1010), a1 = __byte_perm(m1, 0, 0x1010), a2 = __byte_perm(m0, 0, 0x3232), a3 = __byte_perm(m1, 0, 0x3232);
      if (warp == 4) PROF(28);
      if (wg == 1) bar_arrive(NB_TURN, 256);
      wgmma_fence();
      wgmma_n192_rs_ta0_tb1(acc1, a0, a1, a2, a3, make_desc(s16 + kBext / 16, 0, 32, 0), 1);
      wgmma_n48_rs_ta0_tb1(acc2, a0, a1, a2, a3, make_desc(s16 + (kBext + 768) / 16, 0, 32, 0), 1);
      wgmma_commit();
      wgmma_wait<2>();
      if (rel) mbar_arrive_cta(BAR(B_EMPTY), lane);
      const uint2 k0 = lds8(sa + q * 32 + 8), k1 = lds8(sa + q * 32 + 24);
      const float p0 = ldsf(sa + q * 32 - 116), p1 = ldsf(sa + q * 32 - 100);
      tag = __float_as_uint(ldsf(sb + kMisc + 4));
      sg[0] = __byte_perm(__float_as_uint(p0), __float_as_uint(p1), 0x7632); sg[1] = __byte_perm(k0.x, k1.x, 0x7632); sg[2] = __byte_perm(k0.y, k1.y, 0x7632);
      const float sk[4] = {gt0 ? p0 : __uint_as_float(k0.x), gt1 ? p1 : __uint_as_float(k1.x), __uint_as_float(gt0 ? k0.x : k0.y), __uint_as_float(gt1 ? k1.x : k1.y)};
      const float f0 = __uint_as_float(st.z) * (4.47213595499958f / 1.4426950408889634f), f1 = __uint_as_float(st.w) * (4.47213595499958f / 1.4426950408889634f);
#pragma unroll
      for (int i = 0; i < 4; i++) { fs[i] = rcp(sk[i] * (i < 2 ? f0 : f1)); lb[i] = lg2(sk[i]); }
      if (rb + warp == 0) { if (gt0) lb[0] = 1e30f; if (gt1) lb[1] = 1e30f; }
#pragma unroll
      for (int c = 0; c < 10; c++) { acc[4 * c] = bf_lo(xr[c][0]); acc[4 * c + 1] = bf_hi(xr[c][0]); acc[4 * c + 2] = bf_lo(xr[c][1]); acc[4 * c + 3] = bf_hi(xr[c][1]); }
#pragma unroll
      for (int i = 0; i < 40; i++) pin(acc[i]);
#pragma unroll
      for (int i = 0; i < 4; i++) { lb[i] = -lb[i]; pin(fs[i]); pin(lb[i]); }
      pin(sg[0]); pin(sg[1]); pin(sg[2]); pin(ak); pin(ak1); pin(ac); pin(ae); pin(bandm); pin(op);
      if (!wg) mbar_wait(BAR(B_EMPTY), 0);
      if (__float_as_uint(fs[1]) == 0xFFFFFFFFu) return;
      wgmma_wait<0>();
      if (rel) mbar_arrive_cta(BAR(B_EMPTY + 1), lane);
    }
    if ((warp & 3) == 0) PROF2(2, wg);

    auto cvt = [&](int sec, int c, int h) { const float* a = c < 8 ? &acc1[32 * sec + 4 * c + 2 * h] : &acc2[8 * sec + 4 * (c - 8) + 2 * h]; return pack_at(a[0], a[1]); };
    uint32_t qc[10][2], kl[10], kh[10];
    {
      uint32_t vh[10], vl[10];
#pragma unroll
      for (int c = 0; c < 10; c++) { kh[c] = cvt(1, c, 1); vh[c] = cvt(2, c, 1); }
      if (warp == 7) {
        kh[0] = nz(kh[0]); kh[5] = nz(kh[5]); kh[2] = nz(kh[2]); vh[0] = nz(vh[0]); vh[4] = nz(vh[4]);
        uint4* p = UNIT(halo, cta * 160 + lane);
        st_msg_if(rb < 7, p, kh[0], kh[1], kh[3], kh[4]);
        st_msg_if(rb < 7, p + 32, kh[5], kh[6], kh[8], kh[9]);
        st_msg_if(rb < 7, p + 64, kh[2], kh[7], vh[8], vh[9]);
        st_msg_if(rb < 7, p + 96, vh[0], vh[1], vh[2], vh[3]);
        st_msg_if(rb < 7, p + 128, vh[4], vh[5], vh[6], vh[7]);
        bar_arrive(NB_RED, 64);
        PROF(4);
      }
      if (wg) mbar_wait(BAR(B_EMPTY), 0);
      if (warp < 7) {
        sts16(ak + 1280, kh[0], kh[1], kh[3], kh[4]);
        sts16(ak + 1280 + 512, kh[5], kh[6], kh[8], kh[9]);
        sts8(ak1 + 1280, kh[2], kh[7]);
      }
      stsm4(ac + 16 * kPitch, vh[0], vh[1], vh[2], vh[3]);
      stsm4(ac + 16 * kPitch + 64, vh[4], vh[5], vh[6], vh[7]);
      stsm2(ac + 16 * kPitch + 128, vh[8], vh[9]);
      if (warp < 7) bar_arrive(NB_KV + 1 + warp, 64);
#pragma unroll
      for (int c = 0; c < 10; c++) vl[c] = cvt(2, c, 0);
      stsm4(ac + 8 * kPitch, vl[0], vl[1], vl[2], vl[3]);
      stsm4(ac + 8 * kPitch + 64, vl[4], vl[5], vl[6], vl[7]);
      stsm2(ac + 8 * kPitch + 128, vl[8], vl[9]);
#pragma unroll
      for (int c = 0; c < X_NCVT; c++) { qc[c][0] = cvt(0, c, 0); qc[c][1] = cvt(0, c, 1); kl[c] = cvt(1, c, 0); }
      if (__float_as_uint(fs[0]) == 0xFFFFFFFFu) return;
      bar_sync(NB_KV + warp, 64);
    }

    uint32_t ow[10][2];
    auto publish = [&](int s) { st_msg(op + 256 * s, ow[2 * s][0], ow[2 * s][1], ow[2 * s + 1][0], ow[2 * s + 1][1]); };
    {
      const uint2 k2 = lds8(ak1);
#pragma unroll
      for (int p = 0; p < 2; p++) {
        const uint4 u = lds16(ak + 512 * p);
        const uint32_t kp[5] = {u.x, u.y, p ? k2.y : k2.x, u.z, u.w};
        uint32_t vf[5][4];
#pragma unroll
        for (int c = 0; c < 5; c++) ldsm4t(vf[c][0], vf[c][1], vf[c][2], vf[c][3], ae + 80 * p + 16 * c);
        if (p) {
#pragma unroll
          for (int c = X_NCVT; c < 10; c++) { qc[c][0] = cvt(0, c, 0); qc[c][1] = cvt(0, c, 1); kl[c] = cvt(1, c, 0); }
        }
        float s[2][4], mx[2][2];
#pragma unroll
        for (int h = 0; h < 2; h++) {
          const int ca = 5 * p + 3 * h, cm = 5 * p + 2;
          const uint32_t qm0 = (q < 2) == (h == 0) ? qc[cm][0] : 0u, qm1 = (q < 2) == (h == 0) ? qc[cm][1] : 0u;
          float S[3][4];
#pragma unroll
          for (int kt = 2; kt >= 0; kt--) {
            const uint32_t* kk = kt == 0 ? kp - 5 * p : kt == 1 ? kl : kh;
            S[kt][0] = S[kt][1] = S[kt][2] = S[kt][3] = 0.f;
            mma16(S[kt], qc[ca][0], qc[ca][1], qc[ca + 1][0], qc[ca + 1][1], kk[ca], kk[ca + 1]);
            mma8(S[kt], qm0, qm1, kk[cm]);
          }
          s[h][0] = fmaf(gt0 ? S[0][0] : S[1][0], fs[0], lb[0]); s[h][1] = fmaf(gt1 ? S[0][1] : S[1][1], fs[1], lb[1]);
          s[h][2] = fmaf(gt0 ? S[1][2] : S[2][2], fs[2], lb[2]); s[h][3] = fmaf(gt1 ? S[1][3] : S[2][3], fs[3], lb[3]);
          mx[h][0] = fmaxf(s[h][0], s[h][1]); mx[h][1] = fmaxf(s[h][2], s[h][3]);
        }
#pragma unroll
        for (int of = 1; of <= 2; of <<= 1) {
#pragma unroll
          for (int i = 0; i < 4; i++) mx[i >> 1][i & 1] = fmaxf(mx[i >> 1][i & 1], shx(mx[i >> 1][i & 1], of));
        }
#pragma unroll
        for (int r = 1; r >= 0; r--) {
          const uint32_t pk0 = pack_bf16(ex2(s[0][2 * r] - mx[0][r]), ex2(s[0][2 * r + 1] - mx[0][r]));
          const uint32_t pk1 = pack_bf16(ex2(s[1][2 * r] - mx[1][r]), ex2(s[1][2 * r + 1] - mx[1][r]));
          const uint32_t a0 = pk0 & bandm, a1 = pk1 & bandm, a2 = pk0 & ~bandm, a3 = pk1 & ~bandm;
          float l[4] = {0.f, 0.f, 0.f, 0.f};
          mma16(l, a0, a1, a2, a3, sg[r], sg[r + 1]);
          const float i0 = rcp(l[0]), i1 = rcp(l[2]);
#pragma unroll
          for (int c = 0; c < 5; c++) {
            float d[4] = {0.f, 0.f, 0.f, 0.f};
            mma16(d, a0, a1, a2, a3, vf[c][2 * r], vf[c][2 * r + 1]);
            const bool h0 = c < 2 || (c == 2 && q < 2);
            const float i = h0 ? i0 : i1;
            ow[5 * p + c][r] = pack_bf16((h0 ? d[0] : d[2]) * i, (h0 ? d[1] : d[3]) * i);
          }
        }
#pragma unroll
        for (int c = 5 * p + p; c < 5 * p + 5; c += 2) ow[c][0] = lop3<0xEA>(ow[c][0], ~1u, tag);
        if (p == 0) {
          publish(0);
          publish(1);
          if (tag > 1) return;
        }
      }
    }
    if ((warp & 3) == 0) PROF2(7, wg);

    float wr[20], ws = 0.f;
    uint4 *s2w, *s2r;
    {
      uint4 fa[4][7];
      const uint4* fp[7];
#pragma unroll
      for (int i = 1; i < 8; i++) fp[i - 1] = UNIT(obuf, oo ^ (i * 32));
      auto load_round = [&](int s) {
#pragma unroll
        for (int i = 0; i < 7; i++) fa[s & 3][i] = ld_msg(fp[i] + 256 * s);
      };
      auto desc = [&](int i, int s) { return make_desc(s16 + (kWo + i * 10240 + s * 2048) / 16, kWoTail - kWo + (i >> 2) * 10240 + (i & 3) * 32 - i * 10240, 1024, 1); };
      if (X_XO >= 2) publish(2);
      if (X_XO >= 3) publish(3);
      if (X_XO == 3) publish(4);
      mbar_wait(BAR(B_WO), 0);
      if (X_OL == 3) bar_arrive(NB_OL, 288);
      wgmma_fence();
#pragma unroll
      for (int s = 0; s < 5; s++) wgmma_n80_rs_ta0_tb1(acc, ow[2 * s][0], ow[2 * s][1], ow[2 * s + 1][0], ow[2 * s + 1][1], desc(0, s), 1);
      wgmma_commit();
      load_round(0);
      if (X_XO == 2) publish(3);
      load_round(1);
      if (X_XO != 3) publish(4);
      auto mma_round = [&](int s) {
#pragma unroll
        for (int i = 1; i < 8; i++) { const uint4& f = fa[s & 3][i - 1]; wgmma_n80_rs_ta0_tb1(acc, f.x, f.y, f.z, f.w, desc(i, s), 1); }
      };
      wait_round<0>(fa[0], fp, tag, spin);
      wait_round<4096>(fa[1], fp, tag, spin);
      if (warp == 4 * X_PWG) PROF(42);
      if (X_OL == 0) bar_arrive(NB_OL, 288);
      wgmma_fence();
      load_round(2);
      load_round(3);
      mma_round(0);
      mma_round(1);
      wgmma_commit();
      wait_round<8192>(fa[2], fp, tag, spin);
      wait_round<12288>(fa[3], fp, tag, spin);
      if (warp == 4 * X_PWG) PROF(44);
      if (X_OL == 1) bar_arrive(NB_OL, 288);
      wgmma_wait<0>();
      wgmma_fence();
      load_round(4);
      mma_round(2);
      mma_round(3);
      wgmma_commit();
      wait_round<16384>(fa[0], fp, tag, spin);
      if (warp == 4 * X_PWG) PROF(46);
      if (X_OL == 2 && X_UPB == 2) bar_arrive(NB_OL, 288);
      wgmma_fence();
      mma_round(4);
      wgmma_commit();
#pragma unroll
      for (int c = 0; c < 10; c++) { wr[2 * c] = bf_lo(w[c]); wr[2 * c + 1] = bf_hi(w[c]); ws += wr[2 * c] + wr[2 * c + 1]; }
      ws += shx(ws, 1); ws += shx(ws, 2);
#pragma unroll
      for (int i = 0; i < 20; i++) pin(wr[i]);
      ws = __uint_as_float(nz(__float_as_uint(ws)));
      uint32_t l2 = lane;
      pin(l2);
      s2w = UNIT(stat2, tw * 128 + hg * 16 + 8 * (l2 & 3) + (l2 >> 2)); s2r = UNIT(stat2, tw * 128 + l2 + (l2 & 16) * 3);
      pin(ws); pin(s2w); pin(s2r);
      mbar_wait(BAR(B_TAIL), 1);
      if (__float_as_uint(ws) == 0) return;
      wgmma_wait<0>();
    }
    if ((warp & 3) == 0) PROF2(9, wg);

    {
      float t[2][3] = {{0.f, 0.f, 0.f}, {0.f, 0.f, 0.f}};
#pragma unroll
      for (int i = 0; i < 40; i++) {
        float (&u)[3] = t[(i >> 1) & 1];
        u[0] += acc[i]; u[1] = fmaf(acc[i], wr[(i >> 2) * 2 + (i & 1)], u[1]); u[2] = fmaf(acc[i], acc[i], u[2]);
      }
      float v[3];
#pragma unroll
      for (int i = 0; i < 3; i++) v[i] = (q & 1 ? t[1][i] : t[0][i]) + shx(q & 1 ? t[0][i] : t[1][i], 1);
#pragma unroll
      for (int i = 0; i < 3; i++) v[i] += shx(v[i], 2);
      st_msg_if(q < 2, s2w, __float_as_uint(v[0]), __float_as_uint(v[1]), __float_as_uint(v[2]), __float_as_uint(ws));
    }
    const uint32_t t_st2 = (uint32_t)clock64() + X_SWAIT;
    uint32_t hw[10][2];
#pragma unroll
    for (int c = 0; c < 10; c++) { hw[c][0] = pack_at(acc[4 * c], acc[4 * c + 1]); hw[c][1] = pack_at(acc[4 * c + 2], acc[4 * c + 3]); }
    if (warp == 0) PROF(11);
    uint32_t wa[5][2][4], wd[5][4];
    auto load_ffn = [&]() {
      mbar_wait(BAR(B_FFN), 0);
      const uint32_t row = 8 * (m >> 1) + l7;
      const uint32_t ag = sb + kGate + row * 64 + (((2 * wg + (m & 1)) ^ (l7 >> 1)) << 4), ad = sb + kDown + row * 128 + (((m & 1) ^ l7) << 4);
#pragma unroll
      for (int s = 0; s < 5; s++) {
        const uint32_t a = ag + (s < 4 ? (warp & 3) * 4096 + s * 1024 : 16384 + (warp & 3) * 1024);
        ldsm4t(wa[s][0][0], wa[s][0][1], wa[s][0][2], wa[s][0][3], a);
        ldsm4t(wa[s][1][0], wa[s][1][1], wa[s][1][2], wa[s][1][3], a + (kUp - kGate));
        ldsm4t(wd[s][0], wd[s][1], wd[s][2], wd[s][3],
               s < 4 ? (ad ^ (32 * s)) + warp * 2048 : (ad ^ (32 * (warp & 3))) + 16384 + wg * 2048);
      }
    };
    uint32_t wkey, z0, z1;
    {
      uint4 v[4];
      spin_until(t_st2);
#pragma unroll 1
      do {
#pragma unroll
        for (int i = 0; i < 4; i++) v[i] = ld_msg(s2r + 16 * i);
      } while (!all(min(min(v[0].w, v[1].w), min(v[2].w, v[3].w))) && --spin > 0);
      if (warp == 0) PROF(12);
      float sm = (__uint_as_float(v[0].x) + __uint_as_float(v[1].x)) + (__uint_as_float(v[2].x) + __uint_as_float(v[3].x));
      float dt = (__uint_as_float(v[0].y) + __uint_as_float(v[1].y)) + (__uint_as_float(v[2].y) + __uint_as_float(v[3].y));
      float sq = (__uint_as_float(v[0].z) + __uint_as_float(v[1].z)) + (__uint_as_float(v[2].z) + __uint_as_float(v[3].z));
      ws = (__uint_as_float(v[0].w) + __uint_as_float(v[1].w)) + (__uint_as_float(v[2].w) + __uint_as_float(v[3].w));
      sm += shx(sm, 16); sq += shx(sq, 16); dt += shx(dt, 16); ws += shx(ws, 16);
      const float mean = sm * (1.f / 640), rstd = rsq(fmaxf(fmaf(sq, 1.f / 640, -mean * mean), 0.f) + 1e-5f);
      const int sb16 = (int)pack_bf16(0.f, fmaf(-mean, ws, dt) * rstd);
      wkey = __reduce_max_sync(0xffffffffu, ((((uint32_t)(sb16 >> 31) | 0x80000000u) ^ sb16) & 0xFFFF0000u) | (4095 - 256 * rb - par - 32 * warp - 2 * (lane & 15)));
      stsf(sb + kMisc + 16 + warp * 4, __uint_as_float(wkey));
      bar_arrive(NB_KEY, 288);
      if (wkey == 0) return;
      const uint32_t z = pack_bf16(mean, rstd);
      z0 = __shfl_sync(0xffffffffu, z, g); z1 = __shfl_sync(0xffffffffu, z, g + 8);
    }
    const uint32_t crow = (~wkey >> 1) & 15;
    const uint32_t ao = sb + kOutSt + warp * (16 * kPitch);
    {
      const uint32_t m0 = __byte_perm(z0, 0, 0x1010), r0 = __byte_perm(z0, 0, 0x3232), m1 = __byte_perm(z1, 0, 0x1010), r1 = __byte_perm(z1, 0, 0x3232);
      uint32_t cw[10];
#pragma unroll
      for (int c = 0; c < 10; c++) {
        const uint32_t l0 = mul2(sub2(hw[c][0], m0), r0), l1 = mul2(sub2(hw[c][1], m1), r1);
        asm("{\n.reg .pred p;\nsetp.ne.u32 p, %3, 0;\nselp.b32 %0, %1, %2, p;\n}" : "=r"(cw[c]) : "r"(l1), "r"(l0), "r"(crow & 8));
        hw[c][0] = add2(hw[c][0], l0); hw[c][1] = add2(hw[c][1], l1);
      }
      uint4* p = UNIT(cand, tw * 96 + hg * 12 + q);
      st_msg_if(g == (crow & 7), p, lop3<0xEA>(cw[0], ~1u, tag), cw[1], cw[2], cw[3]);
      st_msg_if(g == (crow & 7), p + 4, lop3<0xEA>(cw[4], ~1u, tag), cw[5], cw[6], cw[7]);
      st_msg_if(g == (crow & 7), p + 8, cw[8], cw[9], __byte_perm(cw[0], cw[4], 0x5410), tag);
#pragma unroll
      for (int i = 0; i < 5; i++) stsm4(ao + (lane & 15) * kPitch + (lane & 16) + 32 * i, hw[2 * i][0], hw[2 * i][1], hw[2 * i + 1][0], hw[2 * i + 1][1]);
      stsf(ao + 160, __uint_as_float(crow));
      bar_arrive(wg ? 0 : NB_GRID, 160);
    }
    if (cta < 96) load_ffn();
    bar_sync(NB_KEY + 1, 288);
    const uint32_t gkey = __float_as_uint(ldsf(sb + kMisc + 8));
    auto held_row = [&]() {
      const uint4 v = lds16(ao + crow * kPitch + lane * 16);
      const uint32_t cu = (lane < 8 ? 8 * hg : 56 + 2 * hg) + lane;
      uint4* p = at(gkey == wkey ? P.scr : reinterpret_cast<uint4*>(P.out), (gkey == wkey ? (uint32_t)(offsetof(Scratch, base) / 16) : (~wkey & 2047) * 80) + cu);
      st_msg_if(lane < 10, p, nz(v.x), nz(v.y), nz(v.z), nz(v.w));
    };
    uint4 v[3];
#pragma unroll
    for (int i = 0; i < 3; i++) v[i] = lds16(sb + kSel + ((warp & 3) * 4 + q) * 48 + 16 * i);
    if (cta < 96) {
      if (warp == 0) PROF(16);
      const uint32_t xs[10] = {v[0].x, v[0].y, v[0].z, v[0].w, v[1].x, v[1].y, v[1].z, v[1].w, v[2].x, v[2].y};
      float d[4][4];
#pragma unroll
      for (int i = 0; i < 16; i++) d[i >> 2][i & 3] = 0.f;
#pragma unroll
      for (int s = 0; s < 5; s++) {
        mma16(d[s & 1], wa[s][0][0], wa[s][0][1], wa[s][0][2], wa[s][0][3], xs[2 * s], xs[2 * s + 1]);
        mma16(d[2 + (s & 1)], wa[s][1][0], wa[s][1][1], wa[s][1][2], wa[s][1][3], xs[2 * s], xs[2 * s + 1]);
      }
      {
        uint32_t rs;
        asm("mapa.shared::cluster.u32 %0, %1, %2;" : "=r"(rs) : "r"(sb), "r"(wg));
        if (q == 0)
          asm volatile("st.async.weak.shared::cluster.mbarrier::complete_tx::bytes.v4.f32 [%0], {%1, %2, %3, %4}, [%5];"
                       ::"r"(rs + kPart + (par * 4 + (warp & 3)) * 128 + lane * 4), "f"(d[0][0] + d[1][0]), "f"(d[0][2] + d[1][2]), "f"(d[2][0] + d[3][0]), "f"(d[2][2] + d[3][2]),
                         "r"(rs + kBars + 8 * (B_FULL + 2)) : "memory");
      }
      mbar_wait(BAR(B_FULL + 2), 0);
      float pv[8];
#pragma unroll
      for (int i = 0; i < 8; i++) pv[i] = ldsf(sb + kPart + i * 128 + lane * 4);
      const float gv = bf_round(((pv[0] + pv[1]) + (pv[2] + pv[3])) + ((pv[4] + pv[5]) + (pv[6] + pv[7])));
      const float hid = bf_round(gv * sigmoid(gv)) * shx(gv, 2);
      const uint32_t h0 = pack_bf16(__shfl_sync(0xffffffffu, hid, 8 * q), __shfl_sync(0xffffffffu, hid, 8 * q + 4));
      const uint32_t h1 = pack_bf16(__shfl_sync(0xffffffffu, hid, 8 * q + 1), __shfl_sync(0xffffffffu, hid, 8 * q + 5));
      const uint32_t e0 = g & 1 ? 0u : h0, e1 = g & 1 ? 0u : h1;
      uint4* yp = UNIT(ypart, cta * 192 + warp * 8 + g);
#pragma unroll
      for (int n = 2; n >= 0; n--) {
        float y[4] = {0.f, 0.f, 0.f, 0.f};
        mma16(y, wd[2 * n][0], wd[2 * n][1], wd[2 * n][2], wd[2 * n][3], e0, e1);
        if (n < 2) mma16(y, wd[2 * n + 1][0], wd[2 * n + 1][1], wd[2 * n + 1][2], wd[2 * n + 1][3], h0 ^ e0, h1 ^ e1);
        st_msg_if(q == 0, yp + n * 64, nz(__float_as_uint(y[0])), __float_as_uint(y[1]), __float_as_uint(y[2]), __float_as_uint(y[3]));
      }
      if (warp == 0) PROF(17);
    }
    const uint32_t go = (uint32_t)clock64() + X_YWAIT;
    held_row();
    if (cta < 96 && warp == 0) {
      const uint32_t ch = 4 * (cta >> 5) + (lane & 2) + ((lane >> 2) & 1), col = col_of((cta >> 2) & 7, min(ch, 9u)) + 2 * (cta & 3);
      const float sig = bf_round(sigmoid(__uint_as_float((((uint32_t)((int)~gkey >> 31) | 0x80000000u) ^ gkey) & 0xFFFF0000u)));
      const uint4* p = UNIT(ypart, (lane >> 1) * 192 + 2 * cta + (lane & 1));
      uint4 u[6];
      uint32_t bw;
      spin_until(go);
#pragma unroll 1
      do {
#pragma unroll
        for (int i = 0; i < 6; i++) u[i] = ld_msg(p + 16 * 192 * i);
        bw = ld_word(WORD(base, col >> 1));
      } while (!all(min(min(min(u[0].x, u[1].x), min(u[2].x, u[3].x)), min(min(u[4].x, u[5].x), bw))) && --spin > 0);
      PROF(18);
#define SUM6(c) (((__uint_as_float(u[0].c) + __uint_as_float(u[1].c)) + (__uint_as_float(u[2].c) + __uint_as_float(u[3].c))) + (__uint_as_float(u[4].c) + __uint_as_float(u[5].c)))
      const float y0 = SUM6(x), y1 = SUM6(y), y2 = SUM6(z), y3 = SUM6(w);
#undef SUM6
      const float ya = (lane & 2 ? y1 : y0) + shx(lane & 2 ? y0 : y1, 2), yb = (lane & 2 ? y3 : y2) + shx(lane & 2 ? y2 : y3, 2);
      float y = (lane & 4 ? yb : ya) + shx(lane & 4 ? ya : yb, 4);
      y += shx(y, 8); y += shx(y, 16);
      const uint32_t o = pack_bf16(bf_hi(bw << (~lane & 1) * 16) + bf_round(bf_round(y) * sig), 0.f);
      if (lane < 8 && ch < 10) *at(reinterpret_cast<uint16_t*>(P.out), (~gkey & 2047) * 640 + col + (lane & 1)) = (uint16_t)o;
    }
  }
#undef BAR
#undef UNIT
#undef WORD
}

typedef CUresult (*EncodeTiledFn)(CUtensorMap*, CUtensorMapDataType, cuuint32_t, void*, const cuuint64_t*, const cuuint64_t*, const cuuint32_t*,
                                  const cuuint32_t*, CUtensorMapInterleave, CUtensorMapSwizzle, CUtensorMapL2promotion, CUtensorMapFloatOOBfill);

void make_map(EncodeTiledFn fn, CUtensorMap* m, const void* base, int rank, const cuuint64_t* dims, const cuuint64_t* strides, const cuuint32_t* box,
              CUtensorMapSwizzle swz) {
  const cuuint32_t es[5] = {1, 1, 1, 1, 1};
  fn(m, CU_TENSOR_MAP_DATA_TYPE_BFLOAT16, rank, const_cast<void*>(base), dims, strides, box, es, CU_TENSOR_MAP_INTERLEAVE_NONE, swz,
     box[0] == 16 ? (CUtensorMapL2promotion)X_PROMO : (CUtensorMapL2promotion)X_PROMO2, CU_TENSOR_MAP_FLOAT_OOB_FILL_NONE);
}

}

extern "C" void kernel_launch(void* const* d_in, const int* in_sizes, int n_in, void* d_out, int out_size) {
  (void)in_sizes; (void)n_in; (void)out_size;
  static EncodeTiledFn fn = nullptr;
  static int num_sms = 0;
  static uint4* scr = nullptr;
  static unsigned* count = nullptr;
  if (!fn) {
    int reserved = 0;
    cudaDeviceGetAttribute(&num_sms, cudaDevAttrMultiProcessorCount, 0);
    cudaDeviceGetAttribute(&reserved, cudaDevAttrReservedSharedMemoryPerBlock, 0);
    if (reserved != 1024) num_sms = 0;
    cudaGetSymbolAddress(reinterpret_cast<void**>(&scr), g_scr);
    cudaGetSymbolAddress(reinterpret_cast<void**>(&count), g_count);
    void* p = nullptr;
    cudaDriverEntryPointQueryResult qr;
    cudaGetDriverEntryPoint("cuTensorMapEncodeTiled", &p, cudaEnableDefault, &qr);
    fn = reinterpret_cast<EncodeTiledFn>(p);
    cudaFuncSetAttribute(fused_block_kernel<true>, cudaFuncAttributeMaxDynamicSharedMemorySize, kSmemBytes);
    cudaFuncSetAttribute(fused_block_kernel<false>, cudaFuncAttributeMaxDynamicSharedMemorySize, kSmemBytes);
  }
  Params P;
  P.x = static_cast<const uint8_t*>(d_in[0]);
  P.wqkv = static_cast<const uint8_t*>(d_in[1]);
  P.wo = static_cast<const uint8_t*>(d_in[2]);
  P.wr = static_cast<const uint32_t*>(d_in[4]);
  P.scr = scr;
  P.count = count;
  P.wgate = static_cast<const uint8_t*>(d_in[5]);
  P.wup = static_cast<const uint8_t*>(d_in[6]);
  P.wdown = static_cast<const uint8_t*>(d_in[7]);
  P.out = static_cast<uint8_t*>(d_out);
  { const cuuint64_t d[2] = {1280, 1024}, s[1] = {2560}; const cuuint32_t bx[2] = {64, 64};
    make_map(fn, &P.mx, d_in[0], 2, d, s, bx, CU_TENSOR_MAP_SWIZZLE_128B); }
  { const cuuint64_t d[3] = {640, 640, 3}, s[2] = {3840, 1280}; const cuuint32_t bx[3] = {64, 16, 3}, bx2[3] = {16, 16, 3};
    make_map(fn, &P.mw64, d_in[1], 3, d, s, bx, CU_TENSOR_MAP_SWIZZLE_128B);
    make_map(fn, &P.mw16, d_in[1], 3, d, s, bx2, CU_TENSOR_MAP_SWIZZLE_32B); }
  { const cuuint64_t d[2] = {640, 640}, s[1] = {1280}; const cuuint32_t bx[2] = {64, 80};
    make_map(fn, &P.mwo, d_in[2], 2, d, s, bx, CU_TENSOR_MAP_SWIZZLE_128B); }
  { const cuuint64_t d[3] = {640, 8, 80}, s[2] = {102400, 1280}; const cuuint32_t bx[3] = {16, 4, 20};
    make_map(fn, &P.mtail, d_in[2], 3, d, s, bx, CU_TENSOR_MAP_SWIZZLE_NONE); }
  { const cuuint64_t d[2] = {1536, 640}, s[1] = {3072}; const cuuint32_t bx[2] = {32, 64};
    make_map(fn, &P.mgate, d_in[5], 2, d, s, bx, CU_TENSOR_MAP_SWIZZLE_64B);
    make_map(fn, &P.mup, d_in[6], 2, d, s, bx, CU_TENSOR_MAP_SWIZZLE_64B); }
  { const cuuint64_t d[3] = {64, 1536, 10}, s[2] = {1280, 128}; const cuuint32_t bx[3] = {64, 16, 2};
    make_map(fn, &P.mdown, d_in[7], 3, d, s, bx, CU_TENSOR_MAP_SWIZZLE_128B); }
  if (num_sms == 132) fused_block_kernel<true><<<132, 384, kSmemBytes, cudaStreamPerThread>>>(P.x, P.wqkv, P);
  else fused_block_kernel<false><<<132, 384, kSmemBytes, cudaStreamPerThread>>>(P.x, P.wqkv, P);
}
```

```cpp
#include <cuda_runtime.h>
#include <cuda_bf16.h>
#include <cuda.h>
#include <stdint.h>
#include <stdio.h>

namespace {

constexpr int kStage = 47104;
constexpr int kWo = 0;
constexpr int kKst = 81920;
constexpr int kVst = 92160;
constexpr int kUp = 116736;
constexpr int kDown = 141312;
constexpr int kOutSt = 161792;
constexpr int kPart = 184320;
constexpr int kSel = 185344;
constexpr int kGate = 188416;
constexpr int kNs = 2;
constexpr int kUpSide = kGate + 20480 - 4096 * kNs;
constexpr int kWoTail = 208896;
constexpr int kBars = 229376;
constexpr int kStat = kBars + 128;
constexpr int kBext = kStat + 1152;
constexpr int kMisc = kBext + 1152;
constexpr int kWr = kMisc + 48;
constexpr int kProf = kWr + 192;
constexpr int kSmemBytes = 232448;
constexpr int kPitch = 176;
enum { B_FULL = 0, B_EMPTY = 4, B_AUX = 8, B_WO = 9, B_FFN = 10, B_TAIL = 11, B_HALF = 12 };
enum { NB_TURN = 1, NB_OL = 7, NB_WG = 3, NB_GRID = 5, NB_RED = 6, NB_KV = 8, NB_KEY = 1 };

struct __align__(128) Scratch {
  uint4 obuf[16][8][5][8][32];
  uint4 cand[128][8][3][4];
  uint4 stat1[1024];
  uint4 cs[8][64];
  uint4 halo[14][8][5][32];
  uint32_t hint[2][16][32];
  uint32_t last[32];
  uint32_t keys[16][2];
  uint4 base[8][10];
  uint4 soon[144][8];
  uint4 pad1[544];
  uint4 stat2[16][8][8][16];
  uint4 pad2[512];
  uint4 ypart[96][192];
};
constexpr int kReset1 = 14, kReset2 = 25, kReset = 37;
static_assert(offsetof(Scratch, halo) == offsetof(Scratch, stat1) + 1536 * 16 && offsetof(Scratch, stat2) == offsetof(Scratch, stat1) + 1536 * 16 * kReset1 &&
              offsetof(Scratch, ypart) == offsetof(Scratch, stat1) + 1536 * 16 * kReset2 && sizeof(Scratch) == offsetof(Scratch, stat1) + 1536 * 16 * kReset, "even split");

__device__ Scratch g_scr;
__device__ unsigned g_count[160];
#define PROF(i)
#define PROF2(i, v)
#define PROFG(i)

struct Params {
  const uint8_t* x;
  const uint8_t* wqkv;
  uint4* scr;
  uint8_t* out;
  const uint32_t* wr;
  unsigned* count;
  const uint8_t *wo, *wgate, *wup, *wdown;
  CUtensorMap mx, mw64, mw16, mwo, mtail, mgate, mup, mdown;
};

constexpr int kSpin = 1 << 14;
__device__ __forceinline__ void pin(uint32_t& v) { asm volatile("" : "+r"(v)); }
__device__ __forceinline__ void pin(float& v) { asm volatile("" : "+f"(v)); }
template <class T> __device__ __forceinline__ void pin(T*& v) { asm volatile("" : "+l"(v)); }
template <int N> struct Int { static constexpr int value = N; };

__device__ __forceinline__ uint32_t smem_u32(const void* p) { return (uint32_t)__cvta_generic_to_shared(p); }
__device__ __forceinline__ bool elect() { uint32_t p; asm volatile("{\n.reg .pred p;\nelect.sync _|p, 0xffffffff;\nselp.u32 %0, 1, 0, p;\n}" : "=r"(p)); return p; }
__device__ __forceinline__ void mbar_init(uint32_t bar, uint32_t count) { asm volatile("mbarrier.init.shared::cta.b64 [%0], %1;" ::"r"(bar), "r"(count) : "memory"); }
__device__ __forceinline__ void mbar_expect_tx(uint32_t bar, uint32_t bytes) { asm volatile("mbarrier.arrive.expect_tx.shared::cta.b64 _, [%0], %1;" ::"r"(bar), "r"(bytes) : "memory"); }
__device__ __forceinline__ void mbar_arrive(uint32_t bar) { asm volatile("mbarrier.arrive.shared::cta.b64 _, [%0];" ::"r"(bar) : "memory"); }
__device__ __forceinline__ void mbar_wait(uint32_t bar, uint32_t parity) {
  asm volatile("{\n.reg .pred p;\nWAIT:\nmbarrier.try_wait.parity.shared::cta.b64 p, [%0], %1;\n@!p bra WAIT;\n}" ::"r"(bar), "r"(parity) : "memory");
}
__device__ __forceinline__ void mbar_arrive_cta(uint32_t bar, uint32_t cta) {
  asm volatile("{\n.reg .b32 ra;\nmapa.shared::cluster.u32 ra, %0, %1;\nmbarrier.arrive.shared::cluster.b64 _, [ra];\n}" ::"r"(bar), "r"(cta) : "memory");
}
__device__ __forceinline__ void tma_2d(uint32_t dst, const CUtensorMap* m, uint32_t bar, int c0, int c1) {
  asm volatile("cp.async.bulk.tensor.2d.shared::cluster.global.mbarrier::complete_tx::bytes [%0], [%1, {%3, %4}], [%2];"
               ::"r"(dst), "l"(m), "r"(bar), "r"(c0), "r"(c1) : "memory");
}
__device__ __forceinline__ void tma_3d(uint32_t dst, const CUtensorMap* m, uint32_t bar, int c0, int c1, int c2) {
  asm volatile("cp.async.bulk.tensor.3d.shared::cluster.global.mbarrier::complete_tx::bytes [%0], [%1, {%3, %4, %5}], [%2];"
               ::"r"(dst), "l"(m), "r"(bar), "r"(c0), "r"(c1), "r"(c2) : "memory");
}
__device__ __forceinline__ void tma_3d_mc(uint32_t dst, const CUtensorMap* m, uint32_t bar, int c0, int c1, int c2) {
  asm volatile("cp.async.bulk.tensor.3d.shared::cluster.global.mbarrier::complete_tx::bytes.multicast::cluster [%0], [%1, {%3, %4, %5}], [%2], %6;"
               ::"r"(dst), "l"(m), "r"(bar), "r"(c0), "r"(c1), "r"(c2), "h"((uint16_t)3) : "memory");
}
__device__ __forceinline__ void tma_2d_mc(uint32_t dst, const CUtensorMap* m, uint32_t bar, int c0, int c1) {
  asm volatile("cp.async.bulk.tensor.2d.shared::cluster.global.mbarrier::complete_tx::bytes.multicast::cluster [%0], [%1, {%3, %4}], [%2], %5;"
               ::"r"(dst), "l"(m), "r"(bar), "r"(c0), "r"(c1), "h"((uint16_t)3) : "memory");
}
__device__ __forceinline__ void fence_async() { asm volatile("fence.proxy.async.shared::cta;" ::: "memory"); }
__device__ __forceinline__ void wgmma_fence() { asm volatile("wgmma.fence.sync.aligned;" ::: "memory"); }
__device__ __forceinline__ void wgmma_commit() { asm volatile("wgmma.commit_group.sync.aligned;" ::: "memory"); }
template <int N> __device__ __forceinline__ void wgmma_wait() { asm volatile("wgmma.wait_group.sync.aligned %0;" ::"n"(N) : "memory"); }
__device__ __forceinline__ uint64_t make_desc(uint32_t a16, uint32_t lbo, uint32_t sbo, uint32_t swz) {
  return (uint64_t)(a16 + ((lbo >> 4) << 16)) | ((uint64_t)((sbo >> 4) | (swz << 30)) << 32);
}
__device__ __forceinline__ void bar_sync(int id, int n) { asm volatile("bar.sync %0, %1;" ::"r"(id), "r"(n) : "memory"); }
__device__ __forceinline__ void bar_arrive(int id, int n) { asm volatile("bar.arrive %0, %1;" ::"r"(id), "r"(n) : "memory"); }
__device__ __forceinline__ uint32_t pack_bf16(float lo, float hi) { uint32_t r; asm("cvt.rn.bf16x2.f32 %0, %1, %2;" : "=r"(r) : "f"(hi), "f"(lo)); return r; }
__device__ __forceinline__ uint32_t pack_at(float lo, float hi) { uint32_t r; asm volatile("cvt.rn.bf16x2.f32 %0, %1, %2;" : "=r"(r) : "f"(hi), "f"(lo)); return r; }
__device__ __forceinline__ uint32_t add2(uint32_t a, uint32_t b) { uint32_t r; asm("add.rn.bf16x2 %0, %1, %2;" : "=r"(r) : "r"(a), "r"(b)); return r; }
__device__ __forceinline__ uint32_t sub2(uint32_t a, uint32_t b) { uint32_t r; asm("sub.rn.bf16x2 %0, %1, %2;" : "=r"(r) : "r"(a), "r"(b)); return r; }
__device__ __forceinline__ uint32_t mul2(uint32_t a, uint32_t b) { uint32_t r; asm("mul.rn.bf16x2 %0, %1, %2;" : "=r"(r) : "r"(a), "r"(b)); return r; }
__device__ __forceinline__ float bf_lo(uint32_t w) { return __uint_as_float(w << 16); }
__device__ __forceinline__ float bf_hi(uint32_t w) { return __uint_as_float(w & 0xFFFF0000u); }
__device__ __forceinline__ float bf_round(float v) { return __uint_as_float(pack_bf16(0.f, v)); }
__device__ __forceinline__ float ex2(float v) { float r; asm("ex2.approx.ftz.f32 %0, %1;" : "=f"(r) : "f"(v)); return r; }
__device__ __forceinline__ float rcp(float v) { float r; asm("rcp.approx.ftz.f32 %0, %1;" : "=f"(r) : "f"(v)); return r; }
__device__ __forceinline__ float lg2(float v) { float r; asm("lg2.approx.ftz.f32 %0, %1;" : "=f"(r) : "f"(v)); return r; }
__device__ __forceinline__ float sqr(float v) { float r; asm("sqrt.approx.ftz.f32 %0, %1;" : "=f"(r) : "f"(v)); return r; }
__device__ __forceinline__ float rsq(float v) { float r; asm("rsqrt.approx.ftz.f32 %0, %1;" : "=f"(r) : "f"(v)); return r; }
__device__ __forceinline__ float sigmoid(float v) { return rcp(1.f + ex2(v * -1.4426950408889634f)); }
__device__ __forceinline__ float shx(float v, int o) { return __shfl_xor_sync(0xffffffffu, v, o); }
__device__ __forceinline__ void ldsm4(uint32_t& r0, uint32_t& r1, uint32_t& r2, uint32_t& r3, uint32_t a) { asm volatile("ldmatrix.sync.aligned.m8n8.x4.shared.b16 {%0,%1,%2,%3}, [%4];" : "=r"(r0), "=r"(r1), "=r"(r2), "=r"(r3) : "r"(a) : "memory"); }
__device__ __forceinline__ void ldsm4t(uint32_t& r0, uint32_t& r1, uint32_t& r2, uint32_t& r3, uint32_t a) { asm volatile("ldmatrix.sync.aligned.m8n8.x4.trans.shared.b16 {%0,%1,%2,%3}, [%4];" : "=r"(r0), "=r"(r1), "=r"(r2), "=r"(r3) : "r"(a) : "memory"); }
__device__ __forceinline__ void ldsm2t(uint32_t& r0, uint32_t& r1, uint32_t a) { asm volatile("ldmatrix.sync.aligned.m8n8.x2.trans.shared.b16 {%0,%1}, [%2];" : "=r"(r0), "=r"(r1) : "r"(a) : "memory"); }
__device__ __forceinline__ void stsm4(uint32_t a, uint32_t r0, uint32_t r1, uint32_t r2, uint32_t r3) { asm volatile("stmatrix.sync.aligned.m8n8.x4.shared.b16 [%0], {%1,%2,%3,%4};" ::"r"(a), "r"(r0), "r"(r1), "r"(r2), "r"(r3) : "memory"); }
__device__ __forceinline__ void stsm2(uint32_t a, uint32_t r0, uint32_t r1) { asm volatile("stmatrix.sync.aligned.m8n8.x2.shared.b16 [%0], {%1,%2};" ::"r"(a), "r"(r0), "r"(r1) : "memory"); }
__device__ __forceinline__ uint4 lds16(uint32_t a) { uint4 v; asm volatile("ld.shared.v4.b32 {%0,%1,%2,%3}, [%4];" : "=r"(v.x), "=r"(v.y), "=r"(v.z), "=r"(v.w) : "r"(a) : "memory"); return v; }
__device__ __forceinline__ uint2 lds8(uint32_t a) { uint2 v; asm volatile("ld.shared.v2.b32 {%0,%1}, [%2];" : "=r"(v.x), "=r"(v.y) : "r"(a) : "memory"); return v; }
__device__ __forceinline__ float ldsf(uint32_t a) { float v; asm volatile("ld.shared.f32 %0, [%1];" : "=f"(v) : "r"(a) : "memory"); return v; }
__device__ __forceinline__ void sts16(uint32_t a, uint32_t x, uint32_t y, uint32_t z, uint32_t w) { asm volatile("st.shared.v4.b32 [%0], {%1,%2,%3,%4};" ::"r"(a), "r"(x), "r"(y), "r"(z), "r"(w) : "memory"); }
__device__ __forceinline__ void sts8(uint32_t a, uint32_t x, uint32_t y) { asm volatile("st.shared.v2.b32 [%0], {%1,%2};" ::"r"(a), "r"(x), "r"(y) : "memory"); }
__device__ __forceinline__ void stsf(uint32_t a, float v) { asm volatile("st.shared.f32 [%0], %1;" ::"r"(a), "f"(v) : "memory"); }
__device__ __forceinline__ void mma16(float (&d)[4], uint32_t a0, uint32_t a1, uint32_t a2, uint32_t a3, uint32_t b0, uint32_t b1) {
  asm("mma.sync.aligned.m16n8k16.row.col.f32.bf16.bf16.f32 {%0,%1,%2,%3}, {%4,%5,%6,%7}, {%8,%9}, {%0,%1,%2,%3};"
               : "+f"(d[0]), "+f"(d[1]), "+f"(d[2]), "+f"(d[3]) : "r"(a0), "r"(a1), "r"(a2), "r"(a3), "r"(b0), "r"(b1));
}
__device__ __forceinline__ void mma8(float (&d)[4], uint32_t a0, uint32_t a1, uint32_t b0) {
  asm("mma.sync.aligned.m16n8k8.row.col.f32.bf16.bf16.f32 {%0,%1,%2,%3}, {%4,%5}, {%6}, {%0,%1,%2,%3};"
               : "+f"(d[0]), "+f"(d[1]), "+f"(d[2]), "+f"(d[3]) : "r"(a0), "r"(a1), "r"(b0));
}
__device__ __forceinline__ uint4 ld_msg(const void* p) {
  uint4 v;
  asm volatile("{\n.reg .b128 t;\nld.relaxed.gpu.global.b128 t, [%4];\nmov.b128 {%0, %1, %2, %3}, t;\n}" : "=r"(v.x), "=r"(v.y), "=r"(v.z), "=r"(v.w) : "l"(p) : "memory");
  return v;
}
__device__ __forceinline__ void st_msg(void* p, uint32_t x, uint32_t y, uint32_t z, uint32_t w) {
  asm volatile("{\n.reg .b128 t;\nmov.b128 t, {%1, %2, %3, %4};\nst.relaxed.gpu.global.b128 [%0], t;\n}" ::"l"(p), "r"(x), "r"(y), "r"(z), "r"(w) : "memory");
}
__device__ __forceinline__ void st_msg_if(bool on, void* p, uint32_t x, uint32_t y, uint32_t z, uint32_t w) {
  asm volatile("{\n.reg .b128 t;\n.reg .b64 a, b;\n.reg .pred p;\nsetp.ne.u32 p, %5, 0;\nmov.b64 a, {%1, %2};\nmov.b64 b, {%3, %4};\nmov.b128 t, {a, b};\n@p st.relaxed.gpu.global.b128 [%0], t;\n}"
               ::"l"(p), "r"(x), "r"(y), "r"(z), "r"(w), "r"((uint32_t)on) : "memory");
}
__device__ __forceinline__ void st_word_if(bool on, void* p, uint32_t x) {
  asm volatile("{\n.reg .pred p;\nsetp.ne.u32 p, %2, 0;\n@p st.relaxed.gpu.global.b32 [%0], %1;\n}" ::"l"(p), "r"(x), "r"((uint32_t)on) : "memory");
}
template <int F> __device__ __forceinline__ uint32_t lop3(uint32_t a, uint32_t b, uint32_t c) { uint32_t r; asm("lop3.b32 %0, %1, %2, %3, %4;" : "=r"(r) : "r"(a), "r"(b), "r"(c), "n"(F)); return r; }
__device__ __forceinline__ uint4 ld_words(const void* p) {
  uint4 v;
  asm volatile("ld.relaxed.gpu.global.v4.b32 {%0, %1, %2, %3}, [%4];" : "=r"(v.x), "=r"(v.y), "=r"(v.z), "=r"(v.w) : "l"(p) : "memory");
  return v;
}
__device__ __forceinline__ uint32_t ld_word(const void* p) { uint32_t a; asm volatile("ld.relaxed.gpu.global.b32 %0, [%1];" : "=r"(a) : "l"(p) : "memory"); return a; }
__device__ __forceinline__ void st_word(void* p, uint32_t x) { asm volatile("st.relaxed.gpu.global.b32 [%0], %1;" ::"l"(p), "r"(x) : "memory"); }
__device__ __forceinline__ uint32_t nz(uint32_t w) { uint32_t r; asm("max.u32 %0, %1, 1;" : "=r"(r) : "r"(w)); return r; }
__device__ __forceinline__ bool all(bool p) { return __all_sync(0xffffffffu, p); }
__device__ __forceinline__ uint32_t col_of(uint32_t j, uint32_t c) { return (c < 8 ? 64 * j : 448 + 16 * j) + 8 * c; }
template <class T> __device__ __forceinline__ T* at(T* p, uint32_t i) { T* r; asm("mad.wide.u32 %0, %1, %2, %3;" : "=l"(r) : "r"(i), "n"((int)sizeof(T)), "l"(p)); return r; }
template <int OFF> __device__ __forceinline__ void wait_round(uint4 (&f)[7], const uint4* const (&p)[7], uint32_t tag, int& spin) {
  asm volatile("{\n.reg .pred p;\n.reg .b32 t;\n.reg .b128 v;\nCHECK:\n.pragma \"nounroll\";\n"
    "lop3.b32 t, %0, %4, %36, 0x7E;\n"
    "lop3.b32 t, t, %8, %36, 0xF6;\n"
    "lop3.b32 t, t, %12, %36, 0xF6;\n"
    "lop3.b32 t, t, %16, %36, 0xF6;\n"
    "lop3.b32 t, t, %20, %36, 0xF6;\n"
    "lop3.b32 t, t, %24, %36, 0xF6;\n"
    "and.b32 t, t, 1;\nsetp.eq.u32 p, t, 0;\nvote.sync.all.pred p, p, 0xffffffff;\n@p bra DONE;\n"
    "ld.relaxed.gpu.global.b128 v, [%29 + %37];\nmov.b128 {%0, %1, %2, %3}, v;\n"
    "ld.relaxed.gpu.global.b128 v, [%30 + %37];\nmov.b128 {%4, %5, %6, %7}, v;\n"
    "ld.relaxed.gpu.global.b128 v, [%31 + %37];\nmov.b128 {%8, %9, %10, %11}, v;\n"
    "ld.relaxed.gpu.global.b128 v, [%32 + %37];\nmov.b128 {%12, %13, %14, %15}, v;\n"
    "ld.relaxed.gpu.global.b128 v, [%33 + %37];\nmov.b128 {%16, %17, %18, %19}, v;\n"
    "ld.relaxed.gpu.global.b128 v, [%34 + %37];\nmov.b128 {%20, %21, %22, %23}, v;\n"
    "ld.relaxed.gpu.global.b128 v, [%35 + %37];\nmov.b128 {%24, %25, %26, %27}, v;\n"
    "add.s32 %28, %28, -1;\nsetp.gt.s32 p, %28, 0;\n@p bra CHECK;\nDONE:\n}"
    : "+r"(f[0].x), "+r"(f[0].y), "+r"(f[0].z), "+r"(f[0].w), "+r"(f[1].x), "+r"(f[1].y), "+r"(f[1].z), "+r"(f[1].w), "+r"(f[2].x), "+r"(f[2].y), "+r"(f[2].z), "+r"(f[2].w), "+r"(f[3].x), "+r"(f[3].y), "+r"(f[3].z), "+r"(f[3].w), "+r"(f[4].x), "+r"(f[4].y), "+r"(f[4].z), "+r"(f[4].w), "+r"(f[5].x), "+r"(f[5].y), "+r"(f[5].z), "+r"(f[5].w), "+r"(f[6].x), "+r"(f[6].y), "+r"(f[6].z), "+r"(f[6].w), "+r"(spin)
    : "l"(p[0]), "l"(p[1]), "l"(p[2]), "l"(p[3]), "l"(p[4]), "l"(p[5]), "l"(p[6]), "r"(tag), "n"(OFF) : "memory");
}
__device__ __forceinline__ uint32_t now_ns() { uint32_t t; asm volatile("mov.u32 %0, %%globaltimer_lo;" : "=r"(t)); return t; }
__device__ __forceinline__ uint32_t clock_ordered() { uint32_t t; asm volatile("mov.u32 %0, %%clock;" : "=r"(t) :: "memory"); return t; }
__device__ __forceinline__ void sleep_until(uint32_t t) {
#pragma unroll 1
  while ((int)((uint32_t)clock64() - t) < 0) __nanosleep(100);
}
__device__ __forceinline__ void spin_until(uint32_t t) {
#pragma unroll 1
  while ((int)((uint32_t)clock64() - t) < 0) {}
}

#define X_GAP0 780
#define X_GAP 790
#define X_HWAIT 200
#define X_YWAIT 220
#define X_SWAIT 400
#define X_PWG 0
#define X_ZAT 1000
#define X_TAT 9900
#define X_RWAIT2 14000
#define X_TGAP 150
#define X_WGAP 520
#define X_AWAIT 580
#define X_PF1 700
#define X_GGAP2 230
#define X_SOON 300
#define X_SAT 2700
#define X_HDEL 220
#define X_YNS 1310
#define X_PW (4 * X_PWG)
#define X_MID 5
#define X_PF2 1450
#define X_WD 600
#define X_KNS 1590
#define X_P0 4
#define X_PX 64
#define X_SNS 1000
#define X_NWAIT 400
#define X_LWAIT 300
#define X_NP 1
#define X_KT 250

__device__ __forceinline__ void wgmma_n192_ss_ta0_tb1(float (&d)[96], uint64_t da, uint64_t db, int scale_d) {
  asm volatile("{\n.reg .pred p;\nsetp.ne.b32 p, %98, 0;\n"
    "wgmma.mma_async.sync.aligned.m64n192k16.f32.bf16.bf16 "
    "{%0, %1, %2, %3, %4, %5, %6, %7, %8, %9, %10, %11, %12, %13, %14, %15, "
    "%16, %17, %18, %19, %20, %21, %22, %23, %24, %25, %26, %27, %28, %29, %30, %31, "
    "%32, %33, %34, %35, %36, %37, %38, %39, %40, %41, %42, %43, %44, %45, %46, %47, "
    "%48, %49, %50, %51, %52, %53, %54, %55, %56, %57, %58, %59, %60, %61, %62, %63, "
    "%64, %65, %66, %67, %68, %69, %70, %71, %72, %73, %74, %75, %76, %77, %78, %79, "
    "%80, %81, %82, %83, %84, %85, %86, %87, %88, %89, %90, %91, %92, %93, %94, %95}, "
    "%96, %97, p, 1, 1, 0, 1;\n}\n"
    : "+f"(d[0]), "+f"(d[1]), "+f"(d[2]), "+f"(d[3]), "+f"(d[4]), "+f"(d[5]), "+f"(d[6]), "+f"(d[7]), "+f"(d[8]), "+f"(d[9]), "+f"(d[10]), "+f"(d[11]), "+f"(d[12]), "+f"(d[13]), "+f"(d[14]), "+f"(d[15]), "+f"(d[16]), "+f"(d[17]), "+f"(d[18]), "+f"(d[19]), "+f"(d[20]), "+f"(d[21]), "+f"(d[22]), "+f"(d[23]), "+f"(d[24]), "+f"(d[25]), "+f"(d[26]), "+f"(d[27]), "+f"(d[28]), "+f"(d[29]), "+f"(d[30]), "+f"(d[31]), "+f"(d[32]), "+f"(d[33]), "+f"(d[34]), "+f"(d[35]), "+f"(d[36]), "+f"(d[37]), "+f"(d[38]), "+f"(d[39]), "+f"(d[40]), "+f"(d[41]), "+f"(d[42]), "+f"(d[43]), "+f"(d[44]), "+f"(d[45]), "+f"(d[46]), "+f"(d[47]), "+f"(d[48]), "+f"(d[49]), "+f"(d[50]), "+f"(d[51]), "+f"(d[52]), "+f"(d[53]), "+f"(d[54]), "+f"(d[55]), "+f"(d[56]), "+f"(d[57]), "+f"(d[58]), "+f"(d[59]), "+f"(d[60]), "+f"(d[61]), "+f"(d[62]), "+f"(d[63]), "+f"(d[64]), "+f"(d[65]), "+f"(d[66]), "+f"(d[67]), "+f"(d[68]), "+f"(d[69]), "+f"(d[70]), "+f"(d[71]), "+f"(d[72]), "+f"(d[73]), "+f"(d[74]), "+f"(d[75]), "+f"(d[76]), "+f"(d[77]), "+f"(d[78]), "+f"(d[79]), "+f"(d[80]), "+f"(d[81]), "+f"(d[82]), "+f"(d[83]), "+f"(d[84]), "+f"(d[85]), "+f"(d[86]), "+f"(d[87]), "+f"(d[88]), "+f"(d[89]), "+f"(d[90]), "+f"(d[91]), "+f"(d[92]), "+f"(d[93]), "+f"(d[94]), "+f"(d[95])
    : "l"(da), "l"(db), "r"(scale_d));
}

__device__ __forceinline__ void wgmma_n48_ss_ta0_tb1(float (&d)[24], uint64_t da, uint64_t db, int scale_d) {
  asm volatile("{\n.reg .pred p;\nsetp.ne.b32 p, %26, 0;\n"
    "wgmma.mma_async.sync.aligned.m64n48k16.f32.bf16.bf16 "
    "{%0, %1, %2, %3, %4, %5, %6, %7, %8, %9, %10, %11, %12, %13, %14, %15, "
    "%16, %17, %18, %19, %20, %21, %22, %23}, "
    "%24, %25, p, 1, 1, 0, 1;\n}\n"
    : "+f"(d[0]), "+f"(d[1]), "+f"(d[2]), "+f"(d[3]), "+f"(d[4]), "+f"(d[5]), "+f"(d[6]), "+f"(d[7]), "+f"(d[8]), "+f"(d[9]), "+f"(d[10]), "+f"(d[11]), "+f"(d[12]), "+f"(d[13]), "+f"(d[14]), "+f"(d[15]), "+f"(d[16]), "+f"(d[17]), "+f"(d[18]), "+f"(d[19]), "+f"(d[20]), "+f"(d[21]), "+f"(d[22]), "+f"(d[23])
    : "l"(da), "l"(db), "r"(scale_d));
}

__device__ __forceinline__ void wgmma_n192_rs_ta0_tb1(float (&d)[96], uint32_t a0, uint32_t a1, uint32_t a2, uint32_t a3, uint64_t db, int scale_d) {
  asm volatile("{\n.reg .pred p;\nsetp.ne.b32 p, %101, 0;\n"
    "wgmma.mma_async.sync.aligned.m64n192k16.f32.bf16.bf16 "
    "{%0, %1, %2, %3, %4, %5, %6, %7, %8, %9, %10, %11, %12, %13, %14, %15, "
    "%16, %17, %18, %19, %20, %21, %22, %23, %24, %25, %26, %27, %28, %29, %30, %31, "
    "%32, %33, %34, %35, %36, %37, %38, %39, %40, %41, %42, %43, %44, %45, %46, %47, "
    "%48, %49, %50, %51, %52, %53, %54, %55, %56, %57, %58, %59, %60, %61, %62, %63, "
    "%64, %65, %66, %67, %68, %69, %70, %71, %72, %73, %74, %75, %76, %77, %78, %79, "
    "%80, %81, %82, %83, %84, %85, %86, %87, %88, %89, %90, %91, %92, %93, %94, %95}, "
    "{%96, %97, %98, %99}, %100, p, 1, 1, 1;\n}\n"
    : "+f"(d[0]), "+f"(d[1]), "+f"(d[2]), "+f"(d[3]), "+f"(d[4]), "+f"(d[5]), "+f"(d[6]), "+f"(d[7]), "+f"(d[8]), "+f"(d[9]), "+f"(d[10]), "+f"(d[11]), "+f"(d[12]), "+f"(d[13]), "+f"(d[14]), "+f"(d[15]), "+f"(d[16]), "+f"(d[17]), "+f"(d[18]), "+f"(d[19]), "+f"(d[20]), "+f"(d[21]), "+f"(d[22]), "+f"(d[23]), "+f"(d[24]), "+f"(d[25]), "+f"(d[26]), "+f"(d[27]), "+f"(d[28]), "+f"(d[29]), "+f"(d[30]), "+f"(d[31]), "+f"(d[32]), "+f"(d[33]), "+f"(d[34]), "+f"(d[35]), "+f"(d[36]), "+f"(d[37]), "+f"(d[38]), "+f"(d[39]), "+f"(d[40]), "+f"(d[41]), "+f"(d[42]), "+f"(d[43]), "+f"(d[44]), "+f"(d[45]), "+f"(d[46]), "+f"(d[47]), "+f"(d[48]), "+f"(d[49]), "+f"(d[50]), "+f"(d[51]), "+f"(d[52]), "+f"(d[53]), "+f"(d[54]), "+f"(d[55]), "+f"(d[56]), "+f"(d[57]), "+f"(d[58]), "+f"(d[59]), "+f"(d[60]), "+f"(d[61]), "+f"(d[62]), "+f"(d[63]), "+f"(d[64]), "+f"(d[65]), "+f"(d[66]), "+f"(d[67]), "+f"(d[68]), "+f"(d[69]), "+f"(d[70]), "+f"(d[71]), "+f"(d[72]), "+f"(d[73]), "+f"(d[74]), "+f"(d[75]), "+f"(d[76]), "+f"(d[77]), "+f"(d[78]), "+f"(d[79]), "+f"(d[80]), "+f"(d[81]), "+f"(d[82]), "+f"(d[83]), "+f"(d[84]), "+f"(d[85]), "+f"(d[86]), "+f"(d[87]), "+f"(d[88]), "+f"(d[89]), "+f"(d[90]), "+f"(d[91]), "+f"(d[92]), "+f"(d[93]), "+f"(d[94]), "+f"(d[95])
    : "r"(a0), "r"(a1), "r"(a2), "r"(a3), "l"(db), "r"(scale_d));
}

__device__ __forceinline__ void wgmma_n48_rs_ta0_tb1(float (&d)[24], uint32_t a0, uint32_t a1, uint32_t a2, uint32_t a3, uint64_t db, int scale_d) {
  asm volatile("{\n.reg .pred p;\nsetp.ne.b32 p, %29, 0;\n"
    "wgmma.mma_async.sync.aligned.m64n48k16.f32.bf16.bf16 "
    "{%0, %1, %2, %3, %4, %5, %6, %7, %8, %9, %10, %11, %12, %13, %14, %15, "
    "%16, %17, %18, %19, %20, %21, %22, %23}, "
    "{%24, %25, %26, %27}, %28, p, 1, 1, 1;\n}\n"
    : "+f"(d[0]), "+f"(d[1]), "+f"(d[2]), "+f"(d[3]), "+f"(d[4]), "+f"(d[5]), "+f"(d[6]), "+f"(d[7]), "+f"(d[8]), "+f"(d[9]), "+f"(d[10]), "+f"(d[11]), "+f"(d[12]), "+f"(d[13]), "+f"(d[14]), "+f"(d[15]), "+f"(d[16]), "+f"(d[17]), "+f"(d[18]), "+f"(d[19]), "+f"(d[20]), "+f"(d[21]), "+f"(d[22]), "+f"(d[23])
    : "r"(a0), "r"(a1), "r"(a2), "r"(a3), "l"(db), "r"(scale_d));
}

__device__ __forceinline__ void wgmma_n80_rs_ta0_tb1(float (&d)[40], uint32_t a0, uint32_t a1, uint32_t a2, uint32_t a3, uint64_t db, int scale_d) {
  asm volatile("{\n.reg .pred p;\nsetp.ne.b32 p, %45, 0;\n"
    "wgmma.mma_async.sync.aligned.m64n80k16.f32.bf16.bf16 "
    "{%0, %1, %2, %3, %4, %5, %6, %7, %8, %9, %10, %11, %12, %13, %14, %15, "
    "%16, %17, %18, %19, %20, %21, %22, %23, %24, %25, %26, %27, %28, %29, %30, %31, "
    "%32, %33, %34, %35, %36, %37, %38, %39}, "
    "{%40, %41, %42, %43}, %44, p, 1, 1, 1;\n}\n"
    : "+f"(d[0]), "+f"(d[1]), "+f"(d[2]), "+f"(d[3]), "+f"(d[4]), "+f"(d[5]), "+f"(d[6]), "+f"(d[7]), "+f"(d[8]), "+f"(d[9]), "+f"(d[10]), "+f"(d[11]), "+f"(d[12]), "+f"(d[13]), "+f"(d[14]), "+f"(d[15]), "+f"(d[16]), "+f"(d[17]), "+f"(d[18]), "+f"(d[19]), "+f"(d[20]), "+f"(d[21]), "+f"(d[22]), "+f"(d[23]), "+f"(d[24]), "+f"(d[25]), "+f"(d[26]), "+f"(d[27]), "+f"(d[28]), "+f"(d[29]), "+f"(d[30]), "+f"(d[31]), "+f"(d[32]), "+f"(d[33]), "+f"(d[34]), "+f"(d[35]), "+f"(d[36]), "+f"(d[37]), "+f"(d[38]), "+f"(d[39])
    : "r"(a0), "r"(a1), "r"(a2), "r"(a3), "l"(db), "r"(scale_d));
}

template <bool kUseSmid>
__global__ void __cluster_dims__(2, 1, 1) __launch_bounds__(384, 1) fused_block_kernel(const uint8_t* __restrict__ gx, const uint8_t* __restrict__ gw, const __grid_constant__ Params P) {
  extern __shared__ __align__(1024) uint8_t smem_raw[];
  const uint32_t c_entry = (uint32_t)clock64();
  const uint32_t tid = threadIdx.x;
  uint32_t id = blockIdx.x;
  if (kUseSmid) asm volatile("mov.u32 %0, %%smid;" : "=r"(id));
  const uint32_t sw = __shfl_sync(0xffffffffu, smem_u32(smem_raw) + (id << 12) + (tid >> 5), 0);
  const uint32_t sb = kUseSmid ? sw & 0xFF000400u : smem_u32(smem_raw), warp = sw & 31;
  if (kUseSmid) id = (sw >> 12) & 255;
#define BAR(i) (sb + kBars + 8 * (i))
  if (warp >= 8) {
    if (elect()) {
      const uint32_t cnt = (0x1381u >> (4 * warp - 32)) & 15;
#pragma unroll
      for (int i = 0; i < 4; i++) mbar_init(BAR(4 * (warp - 8) + i), cnt);
      asm volatile("fence.mbarrier_init.release.cluster;" ::: "memory");
    }
    asm volatile("barrier.cluster.arrive.relaxed.aligned;" ::: "memory");
  } else {
    asm volatile("barrier.cluster.arrive.relaxed.aligned;" ::: "memory");
    if (warp != 1 && (warp >= 2 || X_P0 == 4)) {
      const uint32_t t = warp ? (warp - 2) * 4 + (tid & 3) : 24 + (tid & 7), i = (id & 127) * 8 + (t & 7);
      asm volatile("prefetch.global.L2 [%0];" ::"l"((t & 8 ? gx : gw) + (t & 8 ? (i + (i & ~127u) + 128 - (t & 16) * 8) * 10 : i + (t & 16) * 60) * 128));
    }
    if (warp == 1 && elect()) {
#pragma unroll
      for (int i = 0; i < 3; i++) asm volatile("prefetch.tensormap [%0];" ::"l"(&P.mx + i) : "memory");
    }
  }
  if (warp != 8) asm volatile("barrier.cluster.wait.aligned;" ::: "memory");
  const uint32_t lane = __shfl_sync(0xffffffffu, tid & 31, tid & 31);
  const uint32_t tp = id >> 1, par = kUseSmid ? sw >> 24 : id & 1;
  uint32_t beta = tp & 7, idx = tp >> 3;
  if (tp >= 32) { const uint32_t u = tp - 32, d = (u * 37) >> 8, r = u - 7 * d; beta = d < 4 ? 1 + r : 0; idx = d < 4 ? 4 + d : 2 + r; }
  if ((tp >> 1) == 30) {
    const uint32_t h = (id - 120) * 384 + tid;
    uint4* z = P.scr + offsetof(Scratch, stat1) / 16 + h;
#pragma unroll 1
    for (uint32_t n = 0; n < kReset; n++) {
      if (n == 1) { __syncthreads(); spin_until(c_entry + X_ZAT); }
      z[n * 1536] = make_uint4(0, 0, 0, 0);
      if (n == 0 || n == kReset1 - 1 || n == kReset2 - 1 || n == kReset - 1) {
        __syncthreads();
        if (tid == 0) asm volatile("red.release.gpu.global.add.u32 [%0], 1;" ::"l"(P.count + (n / 12 + 1) * 32) : "memory");
      }
      if (n - kReset1 < 5 && h < 1280) asm volatile("prefetch.global.L2 [%0];" ::"l"(P.wo + ((n - kReset1) * 1280 + h) * 128));
    }
    return;
  }
  const uint32_t rb = beta, hg = idx;
  auto half_stage = [&](uint32_t kb, uint32_t h) {
    const uint32_t s = sb + ((kb + 2) & 3) * kStage, fb = BAR((h ? B_FULL : B_HALF) + (kb & 3)), ks = 2 * h + par;
    mbar_expect_tx(fb, kStage / 2);
    tma_3d_mc(s + 16384 + ks * 6144, &P.mw64, fb, 80 * hg, kb * 64 + 16 * ks, 0);
    tma_3d_mc(s + 40960 + ks * 1536, &P.mw16, fb, 80 * hg + 64, kb * 64 + 16 * ks, 0);
    tma_2d(s + 8192 - h * 8192, &P.mx, fb, par * 640 + kb * 64, rb * 128 + 64 - h * 64);
  };
  if (warp == 8) {
    asm volatile("barrier.cluster.wait.aligned;" ::: "memory");
    PROF(1);
    if (elect()) { half_stage(0, 0); half_stage(0, 1); }
  }
  const uint32_t tile = 2 * rb + par, cta = tile * 8 + hg;
  const uint64_t fm = 0xF7F777777777770Full >> (rb * 8 + hg);
  const uint32_t fi = fm & 1 ? 2 * __popcll(fm) - 2 + par : 96;
#define UNIT(field, i) (at(P.scr, i) + offsetof(Scratch, field) / 16)
#define WORD(field, i) (at(reinterpret_cast<uint32_t*>(P.scr), i) + offsetof(Scratch, field) / 4)

  const uint32_t g = lane >> 2, q = lane & 3, m = lane >> 3, l7 = lane & 7;
  int spin = kSpin;

  if (warp >= 8) {
    asm volatile("setmaxnreg.dec.sync.aligned.u32 56;");
    auto permute = [&]() {
      mbar_wait(BAR(B_TAIL), 0);
      PROF(31);
      const uint32_t a = sb + kWoTail + lane * 16, x = (2 * (hg & 3) ^ m) << 4;
#pragma unroll 1
      for (int i = 0; i < 20480; i += 2048) {
        uint4 v[4];
#pragma unroll
        for (int e = 0; e < 4; e++) v[e] = lds16(a + i + e * 512);
        __syncwarp();
#pragma unroll
        for (int e = 0; e < 4; e++) sts16((a ^ x ^ (e & 1) * 64) + i + e * 512, v[e].x, v[e].y, v[e].z, v[e].w);
      }
      fence_async();
      __syncwarp();
      PROF(21);
    };
    auto wait_reset = [&](int i, uint32_t e) {
      unsigned c;
#pragma unroll 1
      do {
        asm volatile("ld.acquire.gpu.global.u32 %0, [%1];" : "=r"(c) : "l"(P.count + i) : "memory");
      } while (c != 4 * e && --spin > 0);
    };
    if (warp == 8) {
      const uint8_t* pf = (lane < 16 ? gx : gw) + (lane < 16 ? (cta * 16 + lane) * 10 : cta * 15 + min(lane, 30u) - 16) * 128;
      auto prefetch = [&]() { pf += lane < 16 ? 128 : 1920 * 128; asm volatile("prefetch.global.L2 [%0];" ::"l"(pf)); };
      spin_until(c_entry + X_PF1);
      prefetch();
      spin_until(c_entry + X_PF2);
      prefetch();
#pragma unroll 1
      for (uint32_t kb = 1; kb < 10; kb++) {
        spin_until(c_entry + X_GAP0 + kb * X_GAP);
        if (kb >= 4) mbar_wait(BAR(B_EMPTY + (kb & 3)), kb >> 3);
        if (elect()) { half_stage(kb, 0); half_stage(kb, 1); }
        if (kb == 10 - kNs) bar_sync(NB_RED, 64);
        if (kb >= 5 && fi < 96 && elect()) {
          const uint32_t n = kb - 5;
          tma_2d(sb + kGate + n * 4096, &P.mgate, BAR(B_FFN), 16 * (fi & ~1u), n < 4 ? 256 * par + 64 * n : 512 + 64 * par);
        }
        if (kb < 8 - kNs) prefetch();
      }
      const uint32_t fc = 16 * (fi & ~1u);
      const bool ffn = fi < 96 && elect();
      if (ffn) {
        mbar_expect_tx(BAR(B_FFN), 61440);
        asm volatile("mbarrier.arrive.shared::cta.b64 _, [%0], 2;" ::"r"(BAR(B_FFN)) : "memory");
      }
#pragma unroll 1
      for (uint32_t n = 0; n < 5; n++) {
        mbar_wait(BAR(B_EMPTY + 2 + (n >= 2)), 1);
        const uint32_t t = (uint32_t)clock64(), i = 2 * n + par;
        if (n < 4 && elect()) tma_2d_mc(sb + kWo + i * 10240, &P.mwo, BAR(B_WO), 64 * hg, 80 * (hg ^ i));
        spin_until(t + X_WGAP);
      }
      if (ffn) mbar_expect_tx(BAR(B_FULL + 2), 1024);
      PROF(20);
      bar_sync(NB_OL, 288);
      uint32_t t = clock_ordered();
#pragma unroll 1
      for (uint32_t n = 0; n < 5; n++) {
        spin_until(t);
        if (fi < 96 && elect()) tma_2d(sb + kUp + n * 4096, &P.mup, BAR(B_FFN), fc, n < 4 ? 256 * par + 64 * n : 512 + 64 * par);
        spin_until(t + X_GGAP2);
        if (fi < 96 && elect()) tma_3d(sb + kDown + n * 4096, &P.mdown, BAR(B_FFN), 0, fc + 16 * par, 2 * n);
        t += 2 * X_GGAP2;
      }
      PROF(60);
      const uint2 et = lds8(sb + kMisc);
      const uint32_t* kp = WORD(keys, 2 * (lane & 15));
      const uint32_t cu = par * 48 + (g & 3) * 12 + q;
      uint32_t k, kt, tn;
      mbar_wait(BAR(B_HALF + 2), 0);
      spin_until((uint32_t)clock64() + X_LWAIT);
#pragma unroll 1
      do { tn = __reduce_max_sync(0xffffffffu, ld_word(WORD(last, lane & 15)) - 1) + 1; } while (!tn && --spin > 0);
      PROF(55);
      tn += X_KNS;
#pragma unroll 1
      while ((int)(now_ns() - tn) < 0) {}
#pragma unroll 1
      do {
        asm volatile("{\n.reg .b64 t;\nld.relaxed.gpu.global.b64 t, [%2];\nmov.b64 {%0, %1}, t;\n}" : "=r"(k), "=r"(kt) : "l"(kp) : "memory");
        k = __reduce_max_sync(0xffffffffu, k - 1) + 1;
      } while (!k && --spin > 0);
      PROF(14);
      const uint4* p = UNIT(cand, ((~k >> 4 & 0x70) + (~k & 1) * 8 + (~k >> 5 & 7)) * 96 + cu);
      bool ok;
#pragma unroll 1
      do {
        if (fi >= 96) { stsf(sb + kMisc + 8, __uint_as_float(k)); break; }
        const uint4 v0 = ld_msg(p), v1 = ld_msg(p + 4), v2 = ld_msg(p + 8);
        sts8(sb + kMisc + 8, k, max(tn, __reduce_max_sync(0xffffffffu, kt) + X_KT));
        sts16(sb + kSel + lane * 48, __byte_perm(v0.x, v2.z, 0x3254), v0.y, v0.z, v0.w);
        sts16(sb + kSel + lane * 48 + 16, __byte_perm(v1.x, v2.z, 0x3276), v1.y, v1.z, v1.w);
        sts8(sb + kSel + lane * 48 + 32, v2.x, v2.y);
        ok = all(!(lop3<0xF6>(lop3<0x7E>(v0.x, v1.x, et.y), v2.w, et.y) & 1));
      } while (!ok && --spin > 0);
      bar_arrive(NB_KEY + 1, 320);
      PROF(15);
      st_word_if(lane + cta == 0, P.count, et.x);
      return;
    }
    const bool sd = warp == 11;
    uint32_t e;
    const uint32_t u = min(tile, 14u);
    if (sd) {
      const uint8_t* sx = gx + (256 * rb + par + 32 * hg + 2 * m) * 1280 + (10 - kNs) * 128 + l7 * 16;
      const uint8_t* sv = gw + (640 - 64 * kNs + (lane >> 1)) * 3840 + (u < 12 ? (u >> 2) * 1280 + (u & 3) * 32 : u * 1280 - 12 * 1280 + 128) + 160 * hg + (lane & 1) * 16;
      e = ld_word(P.count) + 1;
      spin_until(c_entry + X_SAT);
#pragma unroll 1
      for (uint32_t i = 0; i < 4 * kNs; i++) {
        asm volatile("cp.async.cg.shared.global [%0], [%1], 16;" ::"r"(sb + kUpSide + i * 512 + m * 128 + ((l7 ^ m ^ (i & 1) * 4) << 4)), "l"(sx + (i & 3) * 10240 + (i >> 2) * 128) : "memory");
        asm volatile("cp.async.cg.shared.global [%0], [%1], 16;" ::"r"(sb + kUpSide + 2048 * kNs + i * 512 + ((lane ^ (lane >> 3 & 1)) << 4)), "l"(sv + i * (16 * 3840)) : "memory");
      }
      wait_reset(32, e);
      asm volatile("cp.async.wait_all;" ::: "memory");
      __syncwarp();
    }
    bool cw = warp == 10;
    float s0, s1, q0, q1;
#pragma unroll 1
    while (true) {
      uint32_t o0 = ((sd ? 0 : 16 * hg) + (lane & 15)) * 128 + (((m >> 1) ^ l7) << 4), o1 = o0 ^ 32, o2 = o0 ^ 64, o3 = o0 ^ 96;
      if (cw) {
        const bool wide = u < 12 && !sd;
        const uint32_t k = 8 * (m >> 1) + l7, st = wide ? 6144 : sd ? 512 : 1536;
        o0 = wide ? 16384 + (u >> 2) * 2048 + k * 128 + (((2 * (u & 3) + (m & 1)) ^ l7) << 4) : (sd ? 2048 * kNs : 34816 + u * 512) + k * 32 + (((m & 1) ^ (l7 >> 2)) << 4);
        o1 = o0 + st; o2 = o1 + st; o3 = o2 + st;
      }
      s0 = s1 = q0 = q1 = 0.f;
#pragma unroll 1
      for (uint32_t kb = sd ? 10 - 2 * kNs : 0; kb < 10 - kNs; kb++) {
        if (!sd) {
          if (kb == 9 - kNs) {
            bar_sync(NB_GRID, 96);
            const uint4 p = lds16(sb + (cw ? kBext : kStat) + lane * 16);
            s0 += __uint_as_float(p.x); s1 += __uint_as_float(p.y); q0 += __uint_as_float(p.z); q1 += __uint_as_float(p.w);
          }
          mbar_wait(BAR(B_HALF + (kb & 3)), kb >> 2);
          mbar_wait(BAR(B_FULL + (kb & 3)), kb >> 2);
          if (warp == 9) PROF2(47, kb);
        }
        const uint32_t s = sb + (sd ? kUpSide - (10 - 2 * kNs) * 2048 + kb * 2048 : ((kb + 2) & 3) * kStage), a0 = s + o0, a1 = s + o1, a2 = s + o2, a3 = s + o3;
        uint32_t r[16];
        if (cw) { ldsm4t(r[0], r[1], r[2], r[3], a0); ldsm4t(r[4], r[5], r[6], r[7], a1); ldsm4t(r[8], r[9], r[10], r[11], a2); ldsm4t(r[12], r[13], r[14], r[15], a3); }
        else { ldsm4(r[0], r[1], r[2], r[3], a0); ldsm4(r[4], r[5], r[6], r[7], a1); ldsm4(r[8], r[9], r[10], r[11], a2); ldsm4(r[12], r[13], r[14], r[15], a3); }
#pragma unroll
        for (int i = 0; i < 16; i += 2) {
          const float a = bf_lo(r[i]), b = bf_hi(r[i]), c = bf_lo(r[i + 1]), d = bf_hi(r[i + 1]);
          s0 += a; s0 += b; q0 = fmaf(a, a, q0); q0 = fmaf(b, b, q0);
          s1 += c; s1 += d; q1 = fmaf(c, c, q1); q1 = fmaf(d, d, q1);
        }
        if (lane < 2 && !sd) mbar_arrive_cta(BAR(B_EMPTY + (kb & 3)) + (__float_as_uint(q0) >> 31), lane);
      }
      if (!sd) break;
      sts16(sb + (cw ? kBext : kStat) + lane * 16, __float_as_uint(s0), __float_as_uint(s1), __float_as_uint(q0), __float_as_uint(q1));
      if (cw) break;
      cw = true;
    }
    if (warp == 11) {
      PROF(56);
      bar_arrive(NB_GRID, 96);
      bar_arrive(NB_RED, 64);
      if (elect()) {
        mbar_expect_tx(BAR(B_TAIL), 20480);
        asm volatile("mbarrier.arrive.shared::cta.b64 _, [%0], 2;" ::"r"(BAR(B_TAIL)) : "memory");
      }
      if (elect()) {
#pragma unroll 1
        for (int i = 0; i < 5; i++) asm volatile("prefetch.tensormap [%0];" ::"l"(&P.mwo + i) : "memory");
      }
      __syncwarp();
      wait_reset(64, e);
      sts8(sb + kMisc, e, e & 1);
      if (elect()) mbar_arrive(BAR(B_AUX));
      PROF(22);
      {
        const uint32_t w0 = __ldg(at(P.wr, 32 * hg + lane)), w1 = g < 2 ? __ldg(at(P.wr, 8 * hg + lane) + 256) : 0u;
        float s = (bf_lo(w0) + bf_hi(w0)) + (bf_lo(w1) + bf_hi(w1));
#pragma unroll 1
        for (int o = 16; o >= 1; o >>= 1) s += shx(s, o);
        stsf(sb + kWr + q * 48 + g * 4, __uint_as_float(w0));
        stsf(sb + kWr + q * 48 + 32 + min(g, 2u) * 4, g < 2 ? __uint_as_float(w1) : __uint_as_float(nz(__float_as_uint(s))));
      }
      sleep_until(c_entry + X_TAT);
      if (elect()) {
#pragma unroll 1
        for (uint32_t n = 0; n < 4; n++) {
          const uint32_t t = (uint32_t)clock64() + X_TGAP;
          tma_3d_mc(sb + kWoTail + par * 10240 + n * 2560, &P.mtail, BAR(B_TAIL), 512 + 16 * hg, (hg & 4) ^ (4 * par), 20 * n);
          spin_until(t);
        }
      }
      __syncwarp();
      permute();
      if (elect()) asm volatile("mbarrier.arrive.shared::cta.b64 _, [%0], 2;" ::"r"(BAR(B_WO)) : "memory");
      sleep_until(c_entry + X_RWAIT2);
      wait_reset(96, e);
      PROF(30);
      if (elect()) asm volatile("mbarrier.arrive.shared::cta.b64 _, [%0], 3;" ::"r"(BAR(B_TAIL)) : "memory");
    } else {
      PROF2(23, cw);
      s0 = (q & 1 ? s1 : s0) + shx(q & 1 ? s0 : s1, 1); q0 = (q & 1 ? q1 : q0) + shx(q & 1 ? q0 : q1, 1);
      s0 += shx(s0, 2); q0 += shx(q0, 2);
      s0 *= cw ? 1.f : -1.f / 640;
      uint32_t w = pack_bf16(s0, s0 - bf_round(s0));
      const float r = bf_round(sqr(bf_round(bf_round(fmaxf(fmaf(q0, 1.f / 640, -s0 * s0), 0.f)) + 1e-5f)));
      if (cw) asm volatile("movmatrix.sync.aligned.m8n8.trans.b16 %0, %0;" : "+r"(w));
      else if (q & 2) w = __float_as_uint(r);
      const uint32_t src = cw ? (uint32_t)(offsetof(Scratch, cs) / 16) + hg * 64 : (uint32_t)(offsetof(Scratch, stat1) / 16) - 8 + (par * 8 + rb) * 64;
      st_word_if(!cw || lane < 16, WORD(obuf, 4 * src + (cw ? 16 * u : 32 + 32 * hg) + lane), nz(w));
      PROF2(57, cw);
      {
        const uint32_t i0 = (cw || rb) ? lane : max(lane, 8u), i1 = min(lane + 32, cw ? 59u : 63u), i2 = cw ? 59 : 64 + l7;
        uint4 v0, v1, v2;
        spin_until((uint32_t)clock64() + X_AWAIT);
#pragma unroll 1
        do {
          v0 = ld_words(UNIT(obuf, src + i0)); v1 = ld_words(UNIT(obuf, src + i1)); v2 = ld_words(UNIT(obuf, src + i2));
        } while (!all(min(min(min(min(v0.x, v0.y), min(v0.z, v0.w)), min(min(v1.x, v1.y), min(v1.z, v1.w))), min(min(v2.x, v2.y), min(v2.z, v2.w)))) && --spin > 0);
        const uint32_t d = sb + (cw ? kBext : kStat);
        sts16(d + lane * 16, v0.x, v0.y, v0.z, v0.w); sts16(d + 512 + lane * 16, v1.x, v1.y, v1.z, v1.w); sts16(d + 1024 + l7 * 16, v2.x, v2.y, v2.z, v2.w);
      }
      fence_async();
      __syncwarp();
      PROF2(25, cw);
      mbar_wait(BAR(B_FULL + 1), 0);
      if (elect()) mbar_arrive(BAR(B_AUX));
      if (lane < 2) mbar_arrive_cta(BAR(B_EMPTY + 1), lane);
      auto note = [&](int i, uint32_t wait) {
        uint32_t* const hp = WORD(hint, tile * 32 + l7) + 512 * i;
        const uint32_t c = clock_ordered();
        st_word_if(lane == hg, hp, nz(now_ns()));
        spin_until(c + wait);
        uint32_t t;
#pragma unroll 1
        do { t = __reduce_max_sync(0xffffffffu, ld_word(hp) - 1) + 1; } while (!t && --spin > 0);
        return t;
      };
      if (!cw) {
        uint4 v[5];
#pragma unroll
        for (int i = 0; i < 5; i++) v[i] = make_uint4(0, 0, 0, 0);
        mbar_wait(BAR(B_AUX), 0);
        mbar_wait(BAR(B_EMPTY + 3), 1);
        if (rb) {
#pragma unroll 1
          while (!ld_word(UNIT(soon, cta * 8)) && --spin > 0) {}
          spin_until((uint32_t)clock64() + X_SOON);
#pragma unroll 1
          do {
            PROF(5);
#pragma unroll
            for (int i = 0; i < 5; i++) v[i] = ld_msg(UNIT(halo, cta * 160 + lane) + (32 * i - 2560));
          } while (!all(min(min(v[0].x, v[1].x), min(min(v[2].x, v[3].x), v[4].x))) && --spin > 0);
        }
        sts16(sb + kKst + lane * 16, v[0].x, v[0].y, v[0].z, v[0].w);
        sts16(sb + kKst + 512 + lane * 16, v[1].x, v[1].y, v[1].z, v[1].w);
        sts8(sb + kKst + 1024 + lane * 8, v[2].x, v[2].y);
        const uint32_t a = sb + kVst + l7 * kPitch + m * 16;
        stsm4(a, v[3].x, v[3].y, v[3].z, v[3].w);
        stsm4(a + 64, v[4].x, v[4].y, v[4].z, v[4].w);
        stsm2(a + 128, v[2].z, v[2].w);
        bar_arrive(NB_KV, 64);
        PROF(27);
        uint32_t* kp = WORD(keys, 2 * tile);
        mbar_wait(BAR(B_EMPTY + 1), 0);
        bar_sync(NB_KEY, 288);
        const uint32_t tn = now_ns();
        const uint4 ka = lds16(sb + kMisc + 16), kb = lds16(sb + kMisc + 32);
        asm volatile("{\n.reg .pred p;\n.reg .b64 t;\nsetp.eq.u32 p, %3, 0;\nmov.b64 t, {%1, %2};\n@p st.relaxed.gpu.global.b64 [%0], t;\n}"
                     ::"l"(kp), "r"(max(max(max(ka.x, ka.y), max(ka.z, ka.w)), max(max(kb.x, kb.y), max(kb.z, kb.w)))), "r"(tn), "r"(lane + hg) : "memory");
        PROF(13);
        wait_reset(128, __float_as_uint(ldsf(sb + kMisc)));
        PROF(6);
        bar_arrive(NB_KEY + 1, 320);
        return;
      }
      mbar_wait(BAR(B_EMPTY + 1), 0);
      note(0, X_HWAIT);
      spin_until((uint32_t)clock64() + X_HDEL);
      PROF(29);
      if (elect()) mbar_expect_tx(BAR(B_WO), 81920);
      mbar_wait(BAR(B_WO), 0);
      spin_until((uint32_t)clock64() + X_WD);
      if (elect()) mbar_arrive(BAR(B_FULL + 3));
      bar_sync(NB_RED, X_NP == 2 ? 160 : 64);
      const uint32_t tl = note(1, X_NWAIT);
      stsf(sb + kMisc + 12, __uint_as_float(tl));
      st_word_if(lane + hg == 0, WORD(last, tile), tl);
      if (elect()) mbar_arrive(BAR(B_HALF + 2));
      PROF(53);
    }
    bar_sync(warp & 1 ? 0 : NB_GRID, 160);
#pragma unroll 1
    for (uint32_t w = 4 * (warp & 1); w < 4 * (warp & 1) + 4; w++) {
      const uint32_t ao = sb + kOutSt + w * (16 * kPitch), crow = __float_as_uint(ldsf(ao + 160));
      uint4* po = at(reinterpret_cast<uint4*>(P.out), (256 * rb + par + 32 * w) * 80);
#pragma unroll
      for (int i = 0; i < 5; i++) {
        const uint32_t row = i < 4 ? 4 * i + m : lane >> 1, ch = i < 4 ? l7 : 8 + (lane & 1);
        const uint4 v = lds16(ao + row * kPitch + ch * 16);
        if (row != crow) *at(po, row * 160 + (i < 4 ? 8 * hg : 56 + 2 * hg) + ch) = v;
      }
    }
    PROF(59);
  } else {
    asm volatile("setmaxnreg.inc.sync.aligned.u32 224;");
    const uint32_t wg = warp >> 2;
    const uint32_t s16 = kUseSmid ? 64u : (sb & 0x3FFFF) >> 4;
    const bool gt0 = 2 * q > g, gt1 = 2 * q + 1 > g;
    const bool rel = lane + 8 * (warp & 3) < 2;
    float acc1[96], acc2[24];
    const uint32_t ax = sb + (16 * warp + (lane & 15)) * 128 + (((lane >> 4) ^ l7) << 4);
    uint32_t xr[10][2];
    auto wide = [&](uint32_t so, int k, int acc_on) { wgmma_n192_ss_ta0_tb1(acc1, make_desc(s16 + (so >> 4) + wg * 512 + 2 * k, 16, 1024, 1), make_desc(s16 + (so >> 4) + 1024 + 384 * k, 2048, 1024, 1), acc_on); };
    auto slim = [&](uint32_t so, int k, int acc_on) { wgmma_n48_ss_ta0_tb1(acc2, make_desc(s16 + (so >> 4) + wg * 512 + 2 * k, 16, 1024, 1), make_desc(s16 + (so >> 4) + 2560 + 96 * k, 512, 256, 3), acc_on); };
#pragma unroll 1
    for (uint32_t kb = 0;; kb++) {
      const uint32_t so = ((kb + 2) & 3) * kStage;
      if (wg) {
        if (kb >= X_MID) mbar_wait(BAR(B_FULL + (kb & 3)), (kb >> 2) & 1);
        mbar_wait(BAR(B_HALF + (kb & 3)), (kb >> 2) & 1);
      }
      if (warp == 4) PROF2(32, kb);
      wgmma_wait<0>();
      if (rel && kb) mbar_arrive_cta(BAR(B_EMPTY + ((kb - 1) & 3)), lane);
      if (kb == 8) break;
      if (wg == 0 || kb) bar_sync(NB_TURN + wg, 256);
      wgmma_fence();
      wide(so, 0, kb); slim(so, 0, kb); slim(so, 1, 1); wide(so, 1, 1);
      if (wg && kb < X_MID) mbar_wait(BAR(B_FULL + (kb & 3)), (kb >> 2) & 1);
      wide(so, 2, 1); slim(so, 2, 1);
      bar_arrive(NB_TURN + 1 - wg, 256);
      wide(so, 3, 1); slim(so, 3, 1);
      wgmma_commit();
      if (kb == hg) {
#pragma unroll
        for (int i = 0; i < 4; i++) ldsm4(xr[2 * i][0], xr[2 * i][1], xr[2 * i + 1][0], xr[2 * i + 1][1], (ax + so) ^ (32 * i));
        bar_sync(NB_WG + wg, 128);
      }
    }
    auto cvt = [&](int sec, int c, int h) { const float* a = c < 8 ? &acc1[32 * sec + 4 * c + 2 * h] : &acc2[8 * sec + 4 * (c - 8) + 2 * h]; return pack_at(a[0], a[1]); };
    uint32_t tag;
    float fs[4], lb[4];
    uint32_t sg[3];
    const uint32_t sa = sb + kStat + 128 + warp * 128;
#pragma unroll 1
    for (uint32_t ph = wg; ph != wg + 2; ph++) {
      if (ph == 1) {
        if (wg) mbar_wait(BAR(B_HALF + 1), 0);
        bar_sync(NB_TURN + wg, 256);
        wgmma_fence();
#pragma unroll
        for (int k = 0; k < 4; k++) { wide(2 * kStage, k, 1); slim(2 * kStage, k, 1); }
        wide(3 * kStage, 0, 1); slim(3 * kStage, 0, 1); slim(3 * kStage, 1, 1); wide(3 * kStage, 1, 1);
        if (wg) mbar_wait(BAR(B_AUX), 0);
        const uint2 st = lds8(sa + g * 16);
        wide(3 * kStage, 2, 1); slim(3 * kStage, 2, 1); wide(3 * kStage, 3, 1); slim(3 * kStage, 3, 1);
        const uint32_t m0 = q ? 0u : st.x, m1 = q ? 0u : st.y;
        const uint32_t a0 = __byte_perm(m0, 0, 0x1010), a1 = __byte_perm(m1, 0, 0x1010), a2 = __byte_perm(m0, 0, 0x3232), a3 = __byte_perm(m1, 0, 0x3232);
        if (warp == 4) PROF(28);
        if (wg) bar_arrive(NB_TURN, 256);
        st_word_if(lane + (warp ^ 7) == 0, UNIT(soon, cta * 8) + 128, 1);
        wgmma_fence();
        wgmma_n192_rs_ta0_tb1(acc1, a0, a1, a2, a3, make_desc(s16 + kBext / 16, 0, 32, 0), 1);
        wgmma_n48_rs_ta0_tb1(acc2, a0, a1, a2, a3, make_desc(s16 + (kBext + 768) / 16, 0, 32, 0), 1);
        wgmma_commit();
        if (warp == 7 && rb < 7) {
          uint4* p = UNIT(halo, cta * 160 + lane);
          wgmma_wait<0>();
          st_msg(p, nz(cvt(1, 0, 1)), cvt(1, 1, 1), cvt(1, 3, 1), cvt(1, 4, 1));
          st_msg(p + 32, nz(cvt(1, 5, 1)), cvt(1, 6, 1), cvt(1, 8, 1), cvt(1, 9, 1));
          st_msg(p + 64, nz(cvt(1, 2, 1)), cvt(1, 7, 1), cvt(2, 8, 1), cvt(2, 9, 1));
          st_msg(p + 96, nz(cvt(2, 0, 1)), cvt(2, 1, 1), cvt(2, 2, 1), cvt(2, 3, 1));
          st_msg(p + 128, nz(cvt(2, 4, 1)), cvt(2, 5, 1), cvt(2, 6, 1), cvt(2, 7, 1));
          PROF(4);
        }
      } else {
        mbar_wait(wg ? BAR(B_EMPTY + 3) : BAR(B_AUX), wg);
        if (!wg) mbar_wait(BAR(B_FULL), 0);
        ldsm4(xr[8][0], xr[8][1], xr[9][0], xr[9][1], (ax + (2 + (hg >> 2)) * kStage) ^ (32 * (hg & 3)));
        const uint2 so = lds8(sa + g * 16 + 8), k0 = lds8(sa + q * 32 + 8), k1 = lds8(sa + q * 32 + 24);
        const float p0 = ldsf(sa + q * 32 - 116), p1 = ldsf(sa + q * 32 - 100);
        tag = __float_as_uint(ldsf(sb + kMisc + 4));
        sg[0] = __byte_perm(__float_as_uint(p0), __float_as_uint(p1), 0x7632); sg[1] = __byte_perm(k0.x, k1.x, 0x7632); sg[2] = __byte_perm(k0.y, k1.y, 0x7632);
        const float sk[4] = {gt0 ? p0 : __uint_as_float(k0.x), gt1 ? p1 : __uint_as_float(k1.x), __uint_as_float(gt0 ? k0.x : k0.y), __uint_as_float(gt1 ? k1.x : k1.y)};
        const float f0 = __uint_as_float(so.x) * (4.47213595499958f / 1.4426950408889634f), f1 = __uint_as_float(so.y) * (4.47213595499958f / 1.4426950408889634f);
#pragma unroll
        for (int i = 0; i < 4; i++) { fs[i] = rcp(sk[i] * (i < 2 ? f0 : f1)); lb[i] = -lg2(sk[i]); }
        if (rb + warp == 0) { if (gt0) lb[0] = -1e30f; if (gt1) lb[1] = -1e30f; }
      }
    }
    uint32_t ak = sb + kKst + warp * 1280 + lane * 16, ak1 = ak + 1024 - lane * 8, bandm = (gt0 ? 0xFFFFu : 0u) | (gt1 ? 0xFFFF0000u : 0u);
    const uint32_t av = sb + 2 * kStage + warp * 2048 + l7 * kPitch;
    uint32_t ac = av + m * 16, ae = av + (m == 3 ? kStage : m ? 0 : warp ? kStage - 2048 : kVst - 2 * kStage);
    const uint32_t tw = tile * 8 + warp, oo = tw * 1280 + hg * 32 + lane;
    uint4* op = UNIT(obuf, oo);
    float acc[40];
    {
#pragma unroll
      for (int c = 0; c < 10; c++) { acc[4 * c] = bf_lo(xr[c][0]); acc[4 * c + 1] = bf_hi(xr[c][0]); acc[4 * c + 2] = bf_lo(xr[c][1]); acc[4 * c + 3] = bf_hi(xr[c][1]); }
#pragma unroll
      for (int i = 0; i < 40; i++) pin(acc[i]);
      pin(ak); pin(ak1); pin(ac); pin(ae); pin(bandm); pin(op);
      spin_until(c_entry);
      if (__float_as_uint(fs[1]) == 0xFFFFFFFFu) return;
      wgmma_wait<0>();
      if (rel) mbar_arrive_cta(BAR(B_EMPTY + 1), lane);
    }
    if ((warp & 3) == 0) PROF2(2, wg);

    uint32_t qc[10][2], kl[10], kh[10];
    {
      uint32_t vh[10], vl[10];
#pragma unroll
      for (int c = 0; c < 10; c++) kh[c] = cvt(1, c, 1);
      if (warp < 7) {
        sts16(ak + 1280, kh[0], kh[1], kh[3], kh[4]);
        sts16(ak + 1280 + 512, kh[5], kh[6], kh[8], kh[9]);
        sts8(ak1 + 1280, kh[2], kh[7]);
      }
#pragma unroll
      for (int c = 0; c < 10; c++) vh[c] = cvt(2, c, 1);
      stsm4(ac + kStage, vh[0], vh[1], vh[2], vh[3]);
      stsm4(ac + kStage + 64, vh[4], vh[5], vh[6], vh[7]);
      stsm2(ac + kStage + 128, vh[8], vh[9]);
      if (warp < 7) bar_arrive(NB_KV + 1 + warp, 64);
#pragma unroll
      for (int c = 0; c < 10; c++) vl[c] = cvt(2, c, 0);
      stsm4(ac, vl[0], vl[1], vl[2], vl[3]);
      stsm4(ac + 64, vl[4], vl[5], vl[6], vl[7]);
      stsm2(ac + 128, vl[8], vl[9]);
#pragma unroll
      for (int c = 0; c < 10; c++) { qc[c][0] = cvt(0, c, 0); qc[c][1] = cvt(0, c, 1); kl[c] = cvt(1, c, 0); }
      if (__float_as_uint(fs[0]) == 0xFFFFFFFFu) return;
      if (warp == X_PW) PROF(54);
      bar_sync(NB_KV + warp, 64);
    }

    uint32_t ow[10][2];
    auto publish = [&](int s) { st_msg(op + 256 * s, ow[2 * s][0], ow[2 * s][1], ow[2 * s + 1][0], ow[2 * s + 1][1]); };
    {
      const uint2 k2 = lds8(ak1);
#pragma unroll
      for (int p = 0; p < 2; p++) {
        const uint4 u = lds16(ak + 512 * p);
        const uint32_t kp[5] = {u.x, u.y, p ? k2.y : k2.x, u.z, u.w};
        uint32_t vf[5][4];
#pragma unroll
        for (int c = 0; c < 5; c++) {
          ldsm4t(vf[c][0], vf[c][1], vf[c][2], vf[c][3], ae + 80 * p + 16 * c);
        }
        float s[2][4], mx[2][2];
#pragma unroll
        for (int h = 0; h < 2; h++) {
          const int ca = 5 * p + 3 * h, cm = 5 * p + 2;
          const uint32_t qm0 = (q < 2) == (h == 0) ? qc[cm][0] : 0u, qm1 = (q < 2) == (h == 0) ? qc[cm][1] : 0u;
          float S[3][4];
#pragma unroll
          for (int kt = 2; kt >= 0; kt--) {
            const uint32_t* kk = kt == 0 ? kp - 5 * p : kt == 1 ? kl : kh;
            S[kt][0] = S[kt][1] = S[kt][2] = S[kt][3] = 0.f;
            mma16(S[kt], qc[ca][0], qc[ca][1], qc[ca + 1][0], qc[ca + 1][1], kk[ca], kk[ca + 1]);
            mma8(S[kt], qm0, qm1, kk[cm]);
          }
          s[h][0] = fmaf(gt0 ? S[0][0] : S[1][0], fs[0], lb[0]); s[h][1] = fmaf(gt1 ? S[0][1] : S[1][1], fs[1], lb[1]);
          s[h][2] = fmaf(gt0 ? S[1][2] : S[2][2], fs[2], lb[2]); s[h][3] = fmaf(gt1 ? S[1][3] : S[2][3], fs[3], lb[3]);
          mx[h][0] = fmaxf(s[h][0], s[h][1]); mx[h][1] = fmaxf(s[h][2], s[h][3]);
        }
#pragma unroll
        for (int of = 1; of <= 2; of <<= 1) {
#pragma unroll
          for (int i = 0; i < 4; i++) mx[i >> 1][i & 1] = fmaxf(mx[i >> 1][i & 1], shx(mx[i >> 1][i & 1], of));
        }
#pragma unroll
        for (int r = 1; r >= 0; r--) {
          const uint32_t pk0 = pack_bf16(ex2(s[0][2 * r] - mx[0][r]), ex2(s[0][2 * r + 1] - mx[0][r]));
          const uint32_t pk1 = pack_bf16(ex2(s[1][2 * r] - mx[1][r]), ex2(s[1][2 * r + 1] - mx[1][r]));
          const uint32_t a0 = pk0 & bandm, a1 = pk1 & bandm, a2 = pk0 & ~bandm, a3 = pk1 & ~bandm;
          float l[4] = {0.f, 0.f, 0.f, 0.f};
          mma16(l, a0, a1, a2, a3, sg[r], sg[r + 1]);
          const float i0 = rcp(l[0]), i1 = rcp(l[2]);
#pragma unroll
          for (int c = 0; c < 5; c++) {
            float d[4] = {0.f, 0.f, 0.f, 0.f};
            mma16(d, a0, a1, a2, a3, vf[c][2 * r], vf[c][2 * r + 1]);
            const bool h0 = c < 2 || (c == 2 && q < 2);
            const float i = h0 ? i0 : i1;
            ow[5 * p + c][r] = pack_bf16((h0 ? d[0] : d[2]) * i, (h0 ? d[1] : d[3]) * i);
          }
        }
#pragma unroll
        for (int c = 5 * p + p; c < 5 * p + 5; c += 2) ow[c][0] = lop3<0xEA>(ow[c][0], ~1u, tag);
        if (p == 0) {
          publish(0);
          publish(1);
          if (warp == X_PW) PROF(43);
          if (tag > 1) return;
        }
      }
    }
    if ((warp & 3) == 0) PROF2(7, wg);

    uint32_t w[10];
    float wr[20], ws = 0.f;
    uint4 *s2w, *s2r;
    {
      uint4 fa[4][7];
      const uint4* fp[7];
#pragma unroll
      for (int i = 1; i < 8; i++) fp[i - 1] = UNIT(obuf, oo ^ (i * 32));
      auto load_round = [&](int s) {
#pragma unroll
        for (int i = 0; i < 7; i++) fa[s & 3][i] = ld_msg(fp[i] + 256 * s);
      };
      auto desc = [&](int i, int s) { return make_desc(s16 + (kWo + i * 10240 + s * 2048) / 16, kWoTail - kWo + (i >> 2) * 10240 + (i & 3) * 32 - i * 10240, 1024, 1); };
      publish(2);
      mbar_wait(X_WD && !wg ? BAR(B_FULL + 3) : BAR(B_WO), 0);
      if (warp == X_PW) PROF(45);
      wgmma_fence();
#pragma unroll
      for (int s = 0; s < 5; s++) wgmma_n80_rs_ta0_tb1(acc, ow[2 * s][0], ow[2 * s][1], ow[2 * s + 1][0], ow[2 * s + 1][1], desc(0, s), 1);
      wgmma_commit();
      load_round(0);
      publish(3);
      load_round(1);
      publish(4);
      auto mma_round = [&](int s) {
#pragma unroll
        for (int i = 1; i < 8; i++) { const uint4& f = fa[s & 3][i - 1]; wgmma_n80_rs_ta0_tb1(acc, f.x, f.y, f.z, f.w, desc(i, s), 1); }
      };
      wait_round<0>(fa[0], fp, tag, spin);
      wait_round<4096>(fa[1], fp, tag, spin);
      if (warp == X_PW) PROF(42);
      bar_arrive(NB_OL, 288);
      wgmma_fence();
      load_round(2);
      load_round(3);
      mma_round(0);
      mma_round(1);
      wgmma_commit();
      wait_round<8192>(fa[2], fp, tag, spin);
      wait_round<12288>(fa[3], fp, tag, spin);
      if (warp == X_PW) PROF(44);
      if (X_NP == 1 && warp == 0) bar_arrive(NB_RED, 64);
      if (X_NP == 2 && !wg) bar_arrive(NB_RED, 160);
      wgmma_wait<0>();
      wgmma_fence();
      load_round(4);
      mma_round(2);
      mma_round(3);
      wgmma_commit();
      mbar_wait(BAR(B_TAIL), 1);
      wait_round<16384>(fa[0], fp, tag, spin);
      if (warp == X_PW) PROF(46);
      if (X_NP == 0 && warp == 0) bar_arrive(NB_RED, 64);
      {
        const uint4 a = lds16(sb + kWr + q * 48), b = lds16(sb + kWr + q * 48 + 16), c = lds16(sb + kWr + q * 48 + 32);
        w[0] = a.x; w[1] = a.y; w[2] = a.z; w[3] = a.w; w[4] = b.x; w[5] = b.y; w[6] = b.z; w[7] = b.w; w[8] = c.x; w[9] = c.y;
        ws = __uint_as_float(c.z);
      }
      wgmma_fence();
      mma_round(4);
      wgmma_commit();
#pragma unroll
      for (int c = 0; c < 10; c++) { wr[2 * c] = bf_lo(w[c]); wr[2 * c + 1] = bf_hi(w[c]); pin(wr[2 * c]); pin(wr[2 * c + 1]); }
      uint32_t l2 = lane;
      pin(l2);
      s2w = UNIT(stat2, tw * 128 + hg * 16 + 8 * (l2 & 3) + (l2 >> 2)); s2r = UNIT(stat2, tw * 128 + l2 + (l2 & 16) * 3);
      pin(s2w); pin(s2r);
      if (__float_as_uint(ws) == 0) return;
      wgmma_wait<0>();
    }
    if ((warp & 3) == 0) PROF2(9, wg);

    {
      float u[4][3], t[2][3];
#pragma unroll
      for (int i = 0; i < 4; i++) { u[i][0] = acc[i]; u[i][1] = acc[i] * wr[i & 1]; u[i][2] = acc[i] * acc[i]; }
#pragma unroll
      for (int i = 4; i < 40; i++) { u[i & 3][0] += acc[i]; u[i & 3][1] = fmaf(acc[i], wr[(i >> 2) * 2 + (i & 1)], u[i & 3][1]); u[i & 3][2] = fmaf(acc[i], acc[i], u[i & 3][2]); }
#pragma unroll
      for (int i = 0; i < 6; i++) t[i / 3][i % 3] = u[2 * (i / 3)][i % 3] + u[2 * (i / 3) + 1][i % 3];
      float v[3];
#pragma unroll
      for (int i = 0; i < 3; i++) v[i] = (q & 1 ? t[1][i] : t[0][i]) + shx(q & 1 ? t[0][i] : t[1][i], 1);
#pragma unroll
      for (int i = 0; i < 3; i++) v[i] += shx(v[i], 2);
      st_msg_if(q < 2, s2w, __float_as_uint(v[0]), __float_as_uint(v[1]), __float_as_uint(v[2]), __float_as_uint(ws));
    }
    const uint32_t t_st2 = (uint32_t)clock64() + (X_SNS && !wg ? 150 : X_SWAIT);
    uint32_t hw[10][2];
#pragma unroll
    for (int c = 0; c < 10; c++) { hw[c][0] = pack_at(acc[4 * c], acc[4 * c + 1]); hw[c][1] = pack_at(acc[4 * c + 2], acc[4 * c + 3]); }
    if (warp == 0) PROF(11);
    uint32_t wa[5][2][4], wd[5][4];
    auto load_ffn = [&]() {
      mbar_wait(BAR(B_FFN), 0);
      const uint32_t row = 8 * (m >> 1) + l7;
      const uint32_t ag = sb + kGate + row * 64 + (((2 * wg + (m & 1)) ^ (l7 >> 1)) << 4), ad = sb + kDown + row * 128 + (((m & 1) ^ l7) << 4);
#pragma unroll
      for (int s = 0; s < 5; s++) {
        const uint32_t a = ag + (s < 4 ? (warp & 3) * 4096 + s * 1024 : 16384 + (warp & 3) * 1024);
        ldsm4t(wa[s][0][0], wa[s][0][1], wa[s][0][2], wa[s][0][3], a);
        ldsm4t(wa[s][1][0], wa[s][1][1], wa[s][1][2], wa[s][1][3], a + (kUp - kGate));
        ldsm4t(wd[s][0], wd[s][1], wd[s][2], wd[s][3],
               s < 4 ? (ad ^ (32 * s)) + warp * 2048 : (ad ^ (32 * (warp & 3))) + 16384 + wg * 2048);
      }
    };
    uint32_t wkey, z0, z1;
    {
      float mean, rstd;
      uint32_t tk = 4095 - 256 * rb - par - 32 * warp - 2 * (lane & 15);
      pin(tk);
      spin_until(t_st2);
      if (!wg) {
        mbar_wait(BAR(B_HALF + 2), 0);
        const uint32_t due = __float_as_uint(ldsf(sb + kMisc + 12)) + X_SNS;
#pragma unroll 1
        while ((int)(now_ns() - due) < 0) {}
      }
#pragma unroll 1
      do {
        uint4 v[4];
#pragma unroll
        for (int i = 0; i < 4; i++) v[i] = ld_msg(s2r + 16 * i);
#define SUM4(c) ((__uint_as_float(v[0].c) + __uint_as_float(v[1].c)) + (__uint_as_float(v[2].c) + __uint_as_float(v[3].c)))
        float sm = SUM4(x), dt = SUM4(y), sq = SUM4(z), wt = SUM4(w);
#undef SUM4
        sm += shx(sm, 16); sq += shx(sq, 16); dt += shx(dt, 16); wt += shx(wt, 16);
        mean = sm * (1.f / 640);
        rstd = rsq(fmaxf(fmaf(-mean, mean, fmaf(sq, 1.f / 640, 1e-5f)), 1e-5f));
        const int sc = __float_as_int(fmaf(-mean, wt, dt) * rstd);
        const uint32_t low = min(min(v[0].w, v[1].w), min(v[2].w, v[3].w)) ? tk : ~0u;
        wkey = __reduce_max_sync(0xffffffffu, lop3<0xEA>(((uint32_t)(sc >> 31) | 0x80000000u) ^ sc, 0xFFFFF000u, low));
      } while (wkey == ~0u && --spin > 0);
      if (warp == 0) PROF(12);
      stsf(sb + kMisc + 16 + warp * 4, __uint_as_float(wkey));
      bar_arrive(NB_KEY, 288);
      if (wkey == 0) return;
      const uint32_t z = pack_bf16(mean, rstd);
      z0 = __shfl_sync(0xffffffffu, z, g); z1 = __shfl_sync(0xffffffffu, z, g + 8);
    }
    const uint32_t crow = (~wkey >> 1) & 15;
    const uint32_t ao = sb + kOutSt + warp * (16 * kPitch);
    {
      const uint32_t m0 = __byte_perm(z0, 0, 0x1010), r0 = __byte_perm(z0, 0, 0x3232), m1 = __byte_perm(z1, 0, 0x1010), r1 = __byte_perm(z1, 0, 0x3232);
      uint32_t cw[10];
#pragma unroll
      for (int c = 0; c < 10; c++) {
        const uint32_t l0 = mul2(sub2(hw[c][0], m0), r0), l1 = mul2(sub2(hw[c][1], m1), r1);
        asm("{\n.reg .pred p;\nsetp.ne.u32 p, %3, 0;\nselp.b32 %0, %1, %2, p;\n}" : "=r"(cw[c]) : "r"(l1), "r"(l0), "r"(crow & 8));
        hw[c][0] = add2(hw[c][0], l0); hw[c][1] = add2(hw[c][1], l1);
      }
      uint4* p = UNIT(cand, tw * 96 + hg * 12 + q);
      st_msg_if(g == (crow & 7), p, lop3<0xEA>(cw[0], ~1u, tag), cw[1], cw[2], cw[3]);
      st_msg_if(g == (crow & 7), p + 4, lop3<0xEA>(cw[4], ~1u, tag), cw[5], cw[6], cw[7]);
      st_msg_if(g == (crow & 7), p + 8, cw[8], cw[9], __byte_perm(cw[0], cw[4], 0x5410), tag);
#pragma unroll
      for (int i = 0; i < 5; i++) stsm4(ao + (lane & 15) * kPitch + (lane & 16) + 32 * i, hw[2 * i][0], hw[2 * i][1], hw[2 * i + 1][0], hw[2 * i + 1][1]);
      stsf(ao + 160, __uint_as_float(crow));
      bar_arrive(wg ? 0 : NB_GRID, 160);
    }
    uint32_t gkey;
    auto held_row = [&]() {
      const uint4 v = lds16(ao + crow * kPitch + lane * 16);
      const uint32_t cu = (lane < 8 ? 8 * hg : 56 + 2 * hg) + lane;
      uint4* p = at(gkey == wkey ? P.scr : reinterpret_cast<uint4*>(P.out), (gkey == wkey ? (uint32_t)(offsetof(Scratch, base) / 16) : (~wkey & 2047) * 80) + cu);
      st_msg_if(lane < 10, p, nz(v.x), nz(v.y), nz(v.z), nz(v.w));
    };
    if (fi < 96) {
      uint32_t rs;
      asm("mapa.shared::cluster.u32 %0, %1, %2;" : "=r"(rs) : "r"(sb), "r"(wg));
      uint32_t ax2 = sb + kSel + ((warp & 3) * 4 + q) * 48, rp = rs + kPart + (par * 4 + (warp & 3)) * 128 + lane * 4, rbar = rs + kBars + 8 * (B_FULL + 2);
      uint32_t ap = sb + kPart + lane * 4, sl = 8 * q, em = g & 1 ? 0u : ~0u;
      uint4* yp = UNIT(ypart, fi * 192 + q * 64 + warp * 8 + g);
      pin(ax2); pin(rp); pin(rbar); pin(ap); pin(sl); pin(em); pin(yp);
      load_ffn();
      if (wkey == 1) return;
      bar_sync(NB_KEY + 1, 320);
      const uint4 v0 = lds16(ax2), v1 = lds16(ax2 + 16);
      const uint2 v2 = lds8(ax2 + 32);
      gkey = __float_as_uint(ldsf(sb + kMisc + 8));
      if (warp == 0) PROF(16);
      const uint32_t xs[10] = {v0.x, v0.y, v0.z, v0.w, v1.x, v1.y, v1.z, v1.w, v2.x, v2.y};
      float d[4][4];
#pragma unroll
      for (int i = 0; i < 16; i++) d[i >> 2][i & 3] = 0.f;
#pragma unroll
      for (int s = 0; s < 5; s++) {
        mma16(d[s & 1], wa[s][0][0], wa[s][0][1], wa[s][0][2], wa[s][0][3], xs[2 * s], xs[2 * s + 1]);
        mma16(d[2 + (s & 1)], wa[s][1][0], wa[s][1][1], wa[s][1][2], wa[s][1][3], xs[2 * s], xs[2 * s + 1]);
      }
      asm volatile("{\n.reg .pred p;\nsetp.eq.u32 p, %6, 0;\n@p st.async.weak.shared::cluster.mbarrier::complete_tx::bytes.v4.f32 [%0], {%1, %2, %3, %4}, [%5];\n}"
                   ::"r"(rp), "f"(d[0][0] + d[1][0]), "f"(d[0][2] + d[1][2]), "f"(d[2][0] + d[3][0]), "f"(d[2][2] + d[3][2]), "r"(rbar), "r"(sl) : "memory");
      mbar_wait(BAR(B_FULL + 2), 0);
      float pv[8];
#pragma unroll
      for (int i = 0; i < 8; i++) pv[i] = ldsf(ap + i * 128);
      const float gv = bf_round(((pv[0] + pv[1]) + (pv[2] + pv[3])) + ((pv[4] + pv[5]) + (pv[6] + pv[7])));
      const float hid = (gv * shx(gv, 2)) * sigmoid(gv);
      const uint32_t h0 = pack_bf16(__shfl_sync(0xffffffffu, hid, sl), __shfl_sync(0xffffffffu, hid, sl + 4));
      const uint32_t h1 = pack_bf16(__shfl_sync(0xffffffffu, hid, sl + 1), __shfl_sync(0xffffffffu, hid, sl + 5));
      float y[3][4];
#pragma unroll
      for (int n = 0; n < 5; n++) {
        const int t = n < 3 ? 2 * n : 2 * n - 5;
        if (n < 3) y[n][0] = y[n][1] = y[n][2] = y[n][3] = 0.f;
        mma16(y[t >> 1], wd[t][0], wd[t][1], wd[t][2], wd[t][3], n < 3 ? h0 & em : h0 & ~em, n < 3 ? h1 & em : h1 & ~em);
      }
      uint32_t yu[4];
#pragma unroll
      for (int e = 0; e < 4; e++) yu[e] = __float_as_uint(sl == 8 ? y[1][e] : sl ? y[2][e] : y[0][e]);
      st_msg_if(sl < 24, yp, nz(yu[0]), yu[1], yu[2], yu[3]);
      if (warp == 0) PROF(17);
    } else {
      bar_sync(NB_KEY + 1, 320);
      gkey = __float_as_uint(ldsf(sb + kMisc + 8));
    }
    const uint32_t go = (uint32_t)clock64() + X_YWAIT;
    held_row();
    if (fi < 96 && warp == 0) {
      const uint32_t ch = 4 * (fi >> 5) + (lane & 2) + ((lane >> 2) & 1), col = col_of((fi >> 2) & 7, min(ch, 9u)) + 2 * (fi & 3);
      const float sig = bf_round(sigmoid(bf_round(__uint_as_float(((uint32_t)((int)~gkey >> 31) | 0x80000000u) ^ gkey))));
      const uint4* p = UNIT(ypart, (lane >> 1) * 192 + 2 * fi + (lane & 1));
      const uint32_t* pb = WORD(base, col >> 1);
      uint16_t* po = at(reinterpret_cast<uint16_t*>(P.out), (~gkey & 2047) * 640 + col + (lane & 1));
      uint32_t o;
      bool ok;
      spin_until(go);
      const uint32_t gn = __float_as_uint(ldsf(sb + kMisc + 12)) + X_YNS;
#pragma unroll 1
      while ((int)(now_ns() - gn) < 0) {}
#pragma unroll 1
      do {
        uint4 u[6];
        const uint32_t bw = ld_word(pb);
#pragma unroll
        for (int i = 0; i < 6; i++) u[i] = ld_msg(p + 16 * 192 * i);
        ok = all(min(min(min(u[0].x, u[1].x), min(u[2].x, u[3].x)), min(min(u[4].x, u[5].x), bw)));
#define SUM6(c) (((__uint_as_float(u[0].c) + __uint_as_float(u[1].c)) + (__uint_as_float(u[2].c) + __uint_as_float(u[3].c))) + (__uint_as_float(u[4].c) + __uint_as_float(u[5].c)))
        const float y0 = SUM6(x), y1 = SUM6(y), y2 = SUM6(z), y3 = SUM6(w);
#undef SUM6
        const float ya = (lane & 2 ? y1 : y0) + shx(lane & 2 ? y0 : y1, 2), yb = (lane & 2 ? y3 : y2) + shx(lane & 2 ? y2 : y3, 2);
        float y = (lane & 4 ? yb : ya) + shx(lane & 4 ? ya : yb, 4);
        y = (y + shx(y, 8)) + (shx(y, 16) + shx(y, 24));
        o = pack_bf16(fmaf(y, sig, bf_hi(bw << (~lane & 1) * 16)), 0.f);
        asm volatile("{\n.reg .pred p;\nsetp.ne.u32 p, %2, 0;\n@p st.global.u16 [%0], %1;\n}" ::"l"(po), "h"((uint16_t)o), "r"((uint32_t)(ok && lane < 8 && ch < 10)) : "memory");
      } while (!ok && --spin > 0);
    }
  }
#undef BAR
#undef UNIT
#undef WORD
}

typedef CUresult (*EncodeTiledFn)(CUtensorMap*, CUtensorMapDataType, cuuint32_t, void*, const cuuint64_t*, const cuuint64_t*, const cuuint32_t*,
                                  const cuuint32_t*, CUtensorMapInterleave, CUtensorMapSwizzle, CUtensorMapL2promotion, CUtensorMapFloatOOBfill);

void make_map(EncodeTiledFn fn, CUtensorMap* m, const void* base, int rank, const cuuint64_t* dims, const cuuint64_t* strides, const cuuint32_t* box,
              CUtensorMapSwizzle swz) {
  const cuuint32_t es[5] = {1, 1, 1, 1, 1};
  fn(m, CU_TENSOR_MAP_DATA_TYPE_BFLOAT16, rank, const_cast<void*>(base), dims, strides, box, es, CU_TENSOR_MAP_INTERLEAVE_NONE, swz,
     CU_TENSOR_MAP_L2_PROMOTION_L2_128B, CU_TENSOR_MAP_FLOAT_OOB_FILL_NONE);
}

}

extern "C" void kernel_launch(void* const* d_in, const int* in_sizes, int n_in, void* d_out, int out_size) {
  (void)in_sizes; (void)n_in; (void)out_size;
  static EncodeTiledFn fn = nullptr;
  static int num_sms = 0;
  static uint4* scr = nullptr;
  static unsigned* count = nullptr;
  if (!fn) {
    int reserved = 0;
    cudaDeviceGetAttribute(&num_sms, cudaDevAttrMultiProcessorCount, 0);
    cudaDeviceGetAttribute(&reserved, cudaDevAttrReservedSharedMemoryPerBlock, 0);
    if (reserved != 1024) num_sms = 0;
    cudaGetSymbolAddress(reinterpret_cast<void**>(&scr), g_scr);
    cudaGetSymbolAddress(reinterpret_cast<void**>(&count), g_count);
    void* p = nullptr;
    cudaDriverEntryPointQueryResult qr;
    cudaGetDriverEntryPoint("cuTensorMapEncodeTiled", &p, cudaEnableDefault, &qr);
    fn = reinterpret_cast<EncodeTiledFn>(p);
    cudaFuncSetAttribute(fused_block_kernel<true>, cudaFuncAttributeMaxDynamicSharedMemorySize, kSmemBytes);
    cudaFuncSetAttribute(fused_block_kernel<false>, cudaFuncAttributeMaxDynamicSharedMemorySize, kSmemBytes);
  }
  Params P;
  P.x = static_cast<const uint8_t*>(d_in[0]);
  P.wqkv = static_cast<const uint8_t*>(d_in[1]);
  P.wo = static_cast<const uint8_t*>(d_in[2]);
  P.wr = static_cast<const uint32_t*>(d_in[4]);
  P.scr = scr;
  P.count = count;
  P.wgate = static_cast<const uint8_t*>(d_in[5]);
  P.wup = static_cast<const uint8_t*>(d_in[6]);
  P.wdown = static_cast<const uint8_t*>(d_in[7]);
  P.out = static_cast<uint8_t*>(d_out);
  { const cuuint64_t d[2] = {1280, 1024}, s[1] = {2560}; const cuuint32_t bx[2] = {64, 64};
    make_map(fn, &P.mx, d_in[0], 2, d, s, bx, CU_TENSOR_MAP_SWIZZLE_128B); }
  { const cuuint64_t d[3] = {640, 640, 3}, s[2] = {3840, 1280}; const cuuint32_t bx[3] = {64, 16, 3}, bx2[3] = {16, 16, 3};
    make_map(fn, &P.mw64, d_in[1], 3, d, s, bx, CU_TENSOR_MAP_SWIZZLE_128B);
    make_map(fn, &P.mw16, d_in[1], 3, d, s, bx2, CU_TENSOR_MAP_SWIZZLE_32B); }
  { const cuuint64_t d[2] = {640, 640}, s[1] = {1280}; const cuuint32_t bx[2] = {64, 80};
    make_map(fn, &P.mwo, d_in[2], 2, d, s, bx, CU_TENSOR_MAP_SWIZZLE_128B); }
  { const cuuint64_t d[3] = {640, 8, 80}, s[2] = {102400, 1280}; const cuuint32_t bx[3] = {16, 4, 20};
    make_map(fn, &P.mtail, d_in[2], 3, d, s, bx, CU_TENSOR_MAP_SWIZZLE_NONE); }
  { const cuuint64_t d[2] = {1536, 640}, s[1] = {3072}; const cuuint32_t bx[2] = {32, 64};
    make_map(fn, &P.mgate, d_in[5], 2, d, s, bx, CU_TENSOR_MAP_SWIZZLE_64B);
    make_map(fn, &P.mup, d_in[6], 2, d, s, bx, CU_TENSOR_MAP_SWIZZLE_64B); }
  { const cuuint64_t d[3] = {64, 1536, 10}, s[2] = {1280, 128}; const cuuint32_t bx[3] = {64, 16, 2};
    make_map(fn, &P.mdown, d_in[7], 3, d, s, bx, CU_TENSOR_MAP_SWIZZLE_128B); }
  if (num_sms == 132) fused_block_kernel<true><<<132, 384, kSmemBytes, cudaStreamPerThread>>>(P.x, P.wqkv, P);
  else fused_block_kernel<false><<<132, 384, kSmemBytes, cudaStreamPerThread>>>(P.x, P.wqkv, P);
}
```

```cpp
#include <cuda_runtime.h>
#include <cuda_bf16.h>
#include <cuda.h>
#include <stdint.h>
#include <stdio.h>

namespace {

constexpr int kStage = 47104;
constexpr int kWo = 0;
constexpr int kKst = 81920;
constexpr int kVst = 92160;
constexpr int kUp = 116736;
constexpr int kDown = 141312;
constexpr int kOutSt = 161792;
constexpr int kPart = 184320;
constexpr int kSel = 185344;
constexpr int kGate = 188416;
constexpr int kNs = 2;
constexpr int kUpSide = kGate + 20480 - 4096 * kNs;
constexpr int kWoTail = 208896;
constexpr int kBars = 229376;
constexpr int kStat = kBars + 128;
constexpr int kBext = kStat + 1152;
constexpr int kMisc = kBext + 1152;
constexpr int kWr = kMisc + 48;
constexpr int kProf = kWr + 192;
constexpr int kSmemBytes = 232448;
constexpr int kPitch = 176;
enum { B_FULL = 0, B_EMPTY = 4, B_AUX = 8, B_WO = 9, B_FFN = 10, B_TAIL = 11, B_HALF = 12 };
enum { NB_TURN = 1, NB_OL = 7, NB_WG = 3, NB_GRID = 5, NB_RED = 6, NB_KV = 8, NB_KEY = 1 };

struct __align__(128) Scratch {
  uint4 obuf[16][8][5][8][32];
  uint4 cand[128][8][3][4];
  uint4 stat1[1024];
  uint4 cs[8][64];
  uint4 halo[14][8][5][32];
  uint32_t hint[2][16][32];
  uint32_t last[32];
  uint32_t keys[16][2];
  uint4 base[8][10];
  uint4 soon[144][8];
  uint4 pad1[544];
  uint4 stat2[16][8][8][16];
  uint4 pad2[512];
  uint4 ypart[96][192];
};
constexpr int kReset1 = 14, kReset2 = 25, kReset = 37;
static_assert(offsetof(Scratch, halo) == offsetof(Scratch, stat1) + 1536 * 16 && offsetof(Scratch, stat2) == offsetof(Scratch, stat1) + 1536 * 16 * kReset1 &&
              offsetof(Scratch, ypart) == offsetof(Scratch, stat1) + 1536 * 16 * kReset2 && sizeof(Scratch) == offsetof(Scratch, stat1) + 1536 * 16 * kReset, "even split");

__device__ Scratch g_scr;
__device__ unsigned g_count[160];
#define PROF(i)
#define PROF2(i, v)
#define PROFG(i)

struct Params {
  const uint8_t* x;
  const uint8_t* wqkv;
  uint4* scr;
  uint8_t* out;
  const uint32_t* wr;
  unsigned* count;
  const uint8_t *wo, *wgate, *wup, *wdown;
  CUtensorMap mx, mw64, mw16, mwo, mtail, mgate, mup, mdown;
};

constexpr int kSpin = 1 << 16;
__device__ __forceinline__ void pin(uint32_t& v) { asm volatile("" : "+r"(v)); }
__device__ __forceinline__ void pin(float& v) { asm volatile("" : "+f"(v)); }
template <class T> __device__ __forceinline__ void pin(T*& v) { asm volatile("" : "+l"(v)); }
template <int N> struct Int { static constexpr int value = N; };

__device__ __forceinline__ uint32_t smem_u32(const void* p) { return (uint32_t)__cvta_generic_to_shared(p); }
__device__ __forceinline__ bool elect() { uint32_t p; asm volatile("{\n.reg .pred p;\nelect.sync _|p, 0xffffffff;\nselp.u32 %0, 1, 0, p;\n}" : "=r"(p)); return p; }
__device__ __forceinline__ void mbar_init(uint32_t bar, uint32_t count) { asm volatile("mbarrier.init.shared::cta.b64 [%0], %1;" ::"r"(bar), "r"(count) : "memory"); }
__device__ __forceinline__ void mbar_expect_tx(uint32_t bar, uint32_t bytes) { asm volatile("mbarrier.arrive.expect_tx.shared::cta.b64 _, [%0], %1;" ::"r"(bar), "r"(bytes) : "memory"); }
__device__ __forceinline__ void mbar_arrive(uint32_t bar) { asm volatile("mbarrier.arrive.shared::cta.b64 _, [%0];" ::"r"(bar) : "memory"); }
__device__ __forceinline__ void mbar_wait(uint32_t bar, uint32_t parity) {
  asm volatile("{\n.reg .pred p;\nWAIT:\nmbarrier.try_wait.parity.shared::cta.b64 p, [%0], %1;\n@!p bra WAIT;\n}" ::"r"(bar), "r"(parity) : "memory");
}
__device__ __forceinline__ void mbar_arrive_cta(uint32_t bar, uint32_t cta) {
  asm volatile("{\n.reg .b32 ra;\nmapa.shared::cluster.u32 ra, %0, %1;\nmbarrier.arrive.shared::cluster.b64 _, [ra];\n}" ::"r"(bar), "r"(cta) : "memory");
}
__device__ __forceinline__ void tma_2d(uint32_t dst, const CUtensorMap* m, uint32_t bar, int c0, int c1) {
  asm volatile("cp.async.bulk.tensor.2d.shared::cluster.global.mbarrier::complete_tx::bytes [%0], [%1, {%3, %4}], [%2];"
               ::"r"(dst), "l"(m), "r"(bar), "r"(c0), "r"(c1) : "memory");
}
__device__ __forceinline__ void tma_3d(uint32_t dst, const CUtensorMap* m, uint32_t bar, int c0, int c1, int c2) {
  asm volatile("cp.async.bulk.tensor.3d.shared::cluster.global.mbarrier::complete_tx::bytes [%0], [%1, {%3, %4, %5}], [%2];"
               ::"r"(dst), "l"(m), "r"(bar), "r"(c0), "r"(c1), "r"(c2) : "memory");
}
__device__ __forceinline__ void tma_3d_mc(uint32_t dst, const CUtensorMap* m, uint32_t bar, int c0, int c1, int c2) {
  asm volatile("cp.async.bulk.tensor.3d.shared::cluster.global.mbarrier::complete_tx::bytes.multicast::cluster [%0], [%1, {%3, %4, %5}], [%2], %6;"
               ::"r"(dst), "l"(m), "r"(bar), "r"(c0), "r"(c1), "r"(c2), "h"((uint16_t)3) : "memory");
}
__device__ __forceinline__ void tma_2d_mc(uint32_t dst, const CUtensorMap* m, uint32_t bar, int c0, int c1) {
  asm volatile("cp.async.bulk.tensor.2d.shared::cluster.global.mbarrier::complete_tx::bytes.multicast::cluster [%0], [%1, {%3, %4}], [%2], %5;"
               ::"r"(dst), "l"(m), "r"(bar), "r"(c0), "r"(c1), "h"((uint16_t)3) : "memory");
}
__device__ __forceinline__ void fence_async() { asm volatile("fence.proxy.async.shared::cta;" ::: "memory"); }
__device__ __forceinline__ void wgmma_fence() { asm volatile("wgmma.fence.sync.aligned;" ::: "memory"); }
__device__ __forceinline__ void wgmma_commit() { asm volatile("wgmma.commit_group.sync.aligned;" ::: "memory"); }
template <int N> __device__ __forceinline__ void wgmma_wait() { asm volatile("wgmma.wait_group.sync.aligned %0;" ::"n"(N) : "memory"); }
__device__ __forceinline__ uint64_t make_desc(uint32_t a16, uint32_t lbo, uint32_t sbo, uint32_t swz) {
  return (uint64_t)(a16 + ((lbo >> 4) << 16)) | ((uint64_t)((sbo >> 4) | (swz << 30)) << 32);
}
__device__ __forceinline__ void bar_sync(int id, int n) { asm volatile("bar.sync %0, %1;" ::"r"(id), "r"(n) : "memory"); }
__device__ __forceinline__ void bar_arrive(int id, int n) { asm volatile("bar.arrive %0, %1;" ::"r"(id), "r"(n) : "memory"); }
__device__ __forceinline__ uint32_t pack_bf16(float lo, float hi) { uint32_t r; asm("cvt.rn.bf16x2.f32 %0, %1, %2;" : "=r"(r) : "f"(hi), "f"(lo)); return r; }
__device__ __forceinline__ uint32_t pack_at(float lo, float hi) { uint32_t r; asm volatile("cvt.rn.bf16x2.f32 %0, %1, %2;" : "=r"(r) : "f"(hi), "f"(lo)); return r; }
__device__ __forceinline__ uint32_t add2(uint32_t a, uint32_t b) { uint32_t r; asm("add.rn.bf16x2 %0, %1, %2;" : "=r"(r) : "r"(a), "r"(b)); return r; }
__device__ __forceinline__ uint32_t sub2(uint32_t a, uint32_t b) { uint32_t r; asm("sub.rn.bf16x2 %0, %1, %2;" : "=r"(r) : "r"(a), "r"(b)); return r; }
__device__ __forceinline__ uint32_t mul2(uint32_t a, uint32_t b) { uint32_t r; asm("mul.rn.bf16x2 %0, %1, %2;" : "=r"(r) : "r"(a), "r"(b)); return r; }
__device__ __forceinline__ float bf_lo(uint32_t w) { return __uint_as_float(w << 16); }
__device__ __forceinline__ float bf_hi(uint32_t w) { return __uint_as_float(w & 0xFFFF0000u); }
__device__ __forceinline__ float bf_round(float v) { return __uint_as_float(pack_bf16(0.f, v)); }
__device__ __forceinline__ float ex2(float v) { float r; asm("ex2.approx.ftz.f32 %0, %1;" : "=f"(r) : "f"(v)); return r; }
__device__ __forceinline__ float rcp(float v) { float r; asm("rcp.approx.ftz.f32 %0, %1;" : "=f"(r) : "f"(v)); return r; }
__device__ __forceinline__ float lg2(float v) { float r; asm("lg2.approx.ftz.f32 %0, %1;" : "=f"(r) : "f"(v)); return r; }
__device__ __forceinline__ float sqr(float v) { float r; asm("sqrt.approx.ftz.f32 %0, %1;" : "=f"(r) : "f"(v)); return r; }
__device__ __forceinline__ float rsq(float v) { float r; asm("rsqrt.approx.ftz.f32 %0, %1;" : "=f"(r) : "f"(v)); return r; }
__device__ __forceinline__ float sigmoid(float v) { return rcp(1.f + ex2(v * -1.4426950408889634f)); }
__device__ __forceinline__ float shx(float v, int o) { return __shfl_xor_sync(0xffffffffu, v, o); }
__device__ __forceinline__ void ldsm4(uint32_t& r0, uint32_t& r1, uint32_t& r2, uint32_t& r3, uint32_t a) { asm volatile("ldmatrix.sync.aligned.m8n8.x4.shared.b16 {%0,%1,%2,%3}, [%4];" : "=r"(r0), "=r"(r1), "=r"(r2), "=r"(r3) : "r"(a) : "memory"); }
__device__ __forceinline__ void ldsm4t(uint32_t& r0, uint32_t& r1, uint32_t& r2, uint32_t& r3, uint32_t a) { asm volatile("ldmatrix.sync.aligned.m8n8.x4.trans.shared.b16 {%0,%1,%2,%3}, [%4];" : "=r"(r0), "=r"(r1), "=r"(r2), "=r"(r3) : "r"(a) : "memory"); }
__device__ __forceinline__ void ldsm2t(uint32_t& r0, uint32_t& r1, uint32_t a) { asm volatile("ldmatrix.sync.aligned.m8n8.x2.trans.shared.b16 {%0,%1}, [%2];" : "=r"(r0), "=r"(r1) : "r"(a) : "memory"); }
__device__ __forceinline__ void stsm4(uint32_t a, uint32_t r0, uint32_t r1, uint32_t r2, uint32_t r3) { asm volatile("stmatrix.sync.aligned.m8n8.x4.shared.b16 [%0], {%1,%2,%3,%4};" ::"r"(a), "r"(r0), "r"(r1), "r"(r2), "r"(r3) : "memory"); }
__device__ __forceinline__ void stsm2(uint32_t a, uint32_t r0, uint32_t r1) { asm volatile("stmatrix.sync.aligned.m8n8.x2.shared.b16 [%0], {%1,%2};" ::"r"(a), "r"(r0), "r"(r1) : "memory"); }
__device__ __forceinline__ uint4 lds16(uint32_t a) { uint4 v; asm volatile("ld.shared.v4.b32 {%0,%1,%2,%3}, [%4];" : "=r"(v.x), "=r"(v.y), "=r"(v.z), "=r"(v.w) : "r"(a) : "memory"); return v; }
__device__ __forceinline__ uint2 lds8(uint32_t a) { uint2 v; asm volatile("ld.shared.v2.b32 {%0,%1}, [%2];" : "=r"(v.x), "=r"(v.y) : "r"(a) : "memory"); return v; }
__device__ __forceinline__ float ldsf(uint32_t a) { float v; asm volatile("ld.shared.f32 %0, [%1];" : "=f"(v) : "r"(a) : "memory"); return v; }
__device__ __forceinline__ void sts16(uint32_t a, uint32_t x, uint32_t y, uint32_t z, uint32_t w) { asm volatile("st.shared.v4.b32 [%0], {%1,%2,%3,%4};" ::"r"(a), "r"(x), "r"(y), "r"(z), "r"(w) : "memory"); }
__device__ __forceinline__ void sts8(uint32_t a, uint32_t x, uint32_t y) { asm volatile("st.shared.v2.b32 [%0], {%1,%2};" ::"r"(a), "r"(x), "r"(y) : "memory"); }
__device__ __forceinline__ void stsf(uint32_t a, float v) { asm volatile("st.shared.f32 [%0], %1;" ::"r"(a), "f"(v) : "memory"); }
__device__ __forceinline__ void mma16(float (&d)[4], uint32_t a0, uint32_t a1, uint32_t a2, uint32_t a3, uint32_t b0, uint32_t b1) {
  asm("mma.sync.aligned.m16n8k16.row.col.f32.bf16.bf16.f32 {%0,%1,%2,%3}, {%4,%5,%6,%7}, {%8,%9}, {%0,%1,%2,%3};"
               : "+f"(d[0]), "+f"(d[1]), "+f"(d[2]), "+f"(d[3]) : "r"(a0), "r"(a1), "r"(a2), "r"(a3), "r"(b0), "r"(b1));
}
__device__ __forceinline__ void mma8(float (&d)[4], uint32_t a0, uint32_t a1, uint32_t b0) {
  asm("mma.sync.aligned.m16n8k8.row.col.f32.bf16.bf16.f32 {%0,%1,%2,%3}, {%4,%5}, {%6}, {%0,%1,%2,%3};"
               : "+f"(d[0]), "+f"(d[1]), "+f"(d[2]), "+f"(d[3]) : "r"(a0), "r"(a1), "r"(b0));
}
__device__ __forceinline__ uint4 ld_msg(const void* p) {
  uint4 v;
  asm volatile("{\n.reg .b128 t;\nld.relaxed.gpu.global.b128 t, [%4];\nmov.b128 {%0, %1, %2, %3}, t;\n}" : "=r"(v.x), "=r"(v.y), "=r"(v.z), "=r"(v.w) : "l"(p) : "memory");
  return v;
}
__device__ __forceinline__ void st_msg(void* p, uint32_t x, uint32_t y, uint32_t z, uint32_t w) {
  asm volatile("{\n.reg .b128 t;\nmov.b128 t, {%1, %2, %3, %4};\nst.relaxed.gpu.global.b128 [%0], t;\n}" ::"l"(p), "r"(x), "r"(y), "r"(z), "r"(w) : "memory");
}
__device__ __forceinline__ void st_msg_if(bool on, void* p, uint32_t x, uint32_t y, uint32_t z, uint32_t w) {
  asm volatile("{\n.reg .b128 t;\n.reg .b64 a, b;\n.reg .pred p;\nsetp.ne.u32 p, %5, 0;\nmov.b64 a, {%1, %2};\nmov.b64 b, {%3, %4};\nmov.b128 t, {a, b};\n@p st.relaxed.gpu.global.b128 [%0], t;\n}"
               ::"l"(p), "r"(x), "r"(y), "r"(z), "r"(w), "r"((uint32_t)on) : "memory");
}
__device__ __forceinline__ void st_word_if(bool on, void* p, uint32_t x) {
  asm volatile("{\n.reg .pred p;\nsetp.ne.u32 p, %2, 0;\n@p st.relaxed.gpu.global.b32 [%0], %1;\n}" ::"l"(p), "r"(x), "r"((uint32_t)on) : "memory");
}
template <int F> __device__ __forceinline__ uint32_t lop3(uint32_t a, uint32_t b, uint32_t c) { uint32_t r; asm("lop3.b32 %0, %1, %2, %3, %4;" : "=r"(r) : "r"(a), "r"(b), "r"(c), "n"(F)); return r; }
__device__ __forceinline__ uint4 ld_words(const void* p) {
  uint4 v;
  asm volatile("ld.relaxed.gpu.global.v4.b32 {%0, %1, %2, %3}, [%4];" : "=r"(v.x), "=r"(v.y), "=r"(v.z), "=r"(v.w) : "l"(p) : "memory");
  return v;
}
__device__ __forceinline__ uint32_t ld_word(const void* p) { uint32_t a; asm volatile("ld.relaxed.gpu.global.b32 %0, [%1];" : "=r"(a) : "l"(p) : "memory"); return a; }
__device__ __forceinline__ void st_word(void* p, uint32_t x) { asm volatile("st.relaxed.gpu.global.b32 [%0], %1;" ::"l"(p), "r"(x) : "memory"); }
__device__ __forceinline__ uint32_t nz(uint32_t w) { uint32_t r; asm("max.u32 %0, %1, 1;" : "=r"(r) : "r"(w)); return r; }
__device__ __forceinline__ bool all(bool p) { return __all_sync(0xffffffffu, p); }
__device__ __forceinline__ uint32_t col_of(uint32_t j, uint32_t c) { return (c < 8 ? 64 * j : 448 + 16 * j) + 8 * c; }
template <class T> __device__ __forceinline__ T* at(T* p, uint32_t i) { T* r; asm("mad.wide.u32 %0, %1, %2, %3;" : "=l"(r) : "r"(i), "n"((int)sizeof(T)), "l"(p)); return r; }
template <int OFF> __device__ __forceinline__ void wait_round(uint4 (&f)[7], const uint4* const (&p)[7], uint32_t tag, int& spin) {
  asm volatile("{\n.reg .pred p;\n.reg .b32 t;\n.reg .b128 v;\nCHECK:\n.pragma \"nounroll\";\n"
    "lop3.b32 t, %0, %4, %36, 0x7E;\n"
    "lop3.b32 t, t, %8, %36, 0xF6;\n"
    "lop3.b32 t, t, %12, %36, 0xF6;\n"
    "lop3.b32 t, t, %16, %36, 0xF6;\n"
    "lop3.b32 t, t, %20, %36, 0xF6;\n"
    "lop3.b32 t, t, %24, %36, 0xF6;\n"
    "and.b32 t, t, 1;\nsetp.eq.u32 p, t, 0;\nvote.sync.all.pred p, p, 0xffffffff;\n@p bra DONE;\n"
    "ld.relaxed.gpu.global.b128 v, [%29 + %37];\nmov.b128 {%0, %1, %2, %3}, v;\n"
    "ld.relaxed.gpu.global.b128 v, [%30 + %37];\nmov.b128 {%4, %5, %6, %7}, v;\n"
    "ld.relaxed.gpu.global.b128 v, [%31 + %37];\nmov.b128 {%8, %9, %10, %11}, v;\n"
    "ld.relaxed.gpu.global.b128 v, [%32 + %37];\nmov.b128 {%12, %13, %14, %15}, v;\n"
    "ld.relaxed.gpu.global.b128 v, [%33 + %37];\nmov.b128 {%16, %17, %18, %19}, v;\n"
    "ld.relaxed.gpu.global.b128 v, [%34 + %37];\nmov.b128 {%20, %21, %22, %23}, v;\n"
    "ld.relaxed.gpu.global.b128 v, [%35 + %37];\nmov.b128 {%24, %25, %26, %27}, v;\n"
    "add.s32 %28, %28, -1;\nsetp.gt.s32 p, %28, 0;\n@p bra CHECK;\nDONE:\n}"
    : "+r"(f[0].x), "+r"(f[0].y), "+r"(f[0].z), "+r"(f[0].w), "+r"(f[1].x), "+r"(f[1].y), "+r"(f[1].z), "+r"(f[1].w), "+r"(f[2].x), "+r"(f[2].y), "+r"(f[2].z), "+r"(f[2].w), "+r"(f[3].x), "+r"(f[3].y), "+r"(f[3].z), "+r"(f[3].w), "+r"(f[4].x), "+r"(f[4].y), "+r"(f[4].z), "+r"(f[4].w), "+r"(f[5].x), "+r"(f[5].y), "+r"(f[5].z), "+r"(f[5].w), "+r"(f[6].x), "+r"(f[6].y), "+r"(f[6].z), "+r"(f[6].w), "+r"(spin)
    : "l"(p[0]), "l"(p[1]), "l"(p[2]), "l"(p[3]), "l"(p[4]), "l"(p[5]), "l"(p[6]), "r"(tag), "n"(OFF) : "memory");
}
__device__ __forceinline__ uint32_t now_ns() { uint32_t t; asm volatile("mov.u32 %0, %%globaltimer_lo;" : "=r"(t)); return t; }
__device__ __forceinline__ void until_ns(uint32_t t) {
#pragma unroll 1
  while (t - now_ns() - 1 < 4096u) {}
}
__device__ __forceinline__ uint32_t clock_ordered() { uint32_t t; asm volatile("mov.u32 %0, %%clock;" : "=r"(t) :: "memory"); return t; }
__device__ __forceinline__ void sleep_until(uint32_t t) {
#pragma unroll 1
  while ((int)((uint32_t)clock64() - t) < 0) __nanosleep(100);
}
__device__ __forceinline__ void spin_until(uint32_t t) {
#pragma unroll 1
  while ((int)((uint32_t)clock64() - t) < 0) {}
}

#define X_GAP0 690
#define X_GAP 790
#define X_HWAIT 380
#define X_YWAIT 220
#define X_SWAIT 400
#define X_PWG 0
#define X_ZAT 1000
#define X_TAT 9900
#define X_TGAP 150
#define X_WGAP 400
#define X_AWAIT 580
#define X_PF1 1050
#define X_GGAP2 230
#define X_SOON 300
#define X_SAT 2700
#define X_GNS 640
#define X_YNS 1310
#define X_PW (4 * X_PWG)
#define X_MID 8
#define X_WD 370
#define X_KNS 1590
#define X_SNS 1000
#define X_NWAIT 400
#define X_LWAIT 300
#define X_PFC 2
#define X_PFD 430
#define X_AD3 350
#define X_ADW 0
#define X_PB 4
#define X_W0 0
#define X_KT 250

__device__ __forceinline__ void wgmma_n192_ss_ta0_tb1(float (&d)[96], uint64_t da, uint64_t db, int scale_d) {
  asm volatile("{\n.reg .pred p;\nsetp.ne.b32 p, %98, 0;\n"
    "wgmma.mma_async.sync.aligned.m64n192k16.f32.bf16.bf16 "
    "{%0, %1, %2, %3, %4, %5, %6, %7, %8, %9, %10, %11, %12, %13, %14, %15, "
    "%16, %17, %18, %19, %20, %21, %22, %23, %24, %25, %26, %27, %28, %29, %30, %31, "
    "%32, %33, %34, %35, %36, %37, %38, %39, %40, %41, %42, %43, %44, %45, %46, %47, "
    "%48, %49, %50, %51, %52, %53, %54, %55, %56, %57, %58, %59, %60, %61, %62, %63, "
    "%64, %65, %66, %67, %68, %69, %70, %71, %72, %73, %74, %75, %76, %77, %78, %79, "
    "%80, %81, %82, %83, %84, %85, %86, %87, %88, %89, %90, %91, %92, %93, %94, %95}, "
    "%96, %97, p, 1, 1, 0, 1;\n}\n"
    : "+f"(d[0]), "+f"(d[1]), "+f"(d[2]), "+f"(d[3]), "+f"(d[4]), "+f"(d[5]), "+f"(d[6]), "+f"(d[7]), "+f"(d[8]), "+f"(d[9]), "+f"(d[10]), "+f"(d[11]), "+f"(d[12]), "+f"(d[13]), "+f"(d[14]), "+f"(d[15]), "+f"(d[16]), "+f"(d[17]), "+f"(d[18]), "+f"(d[19]), "+f"(d[20]), "+f"(d[21]), "+f"(d[22]), "+f"(d[23]), "+f"(d[24]), "+f"(d[25]), "+f"(d[26]), "+f"(d[27]), "+f"(d[28]), "+f"(d[29]), "+f"(d[30]), "+f"(d[31]), "+f"(d[32]), "+f"(d[33]), "+f"(d[34]), "+f"(d[35]), "+f"(d[36]), "+f"(d[37]), "+f"(d[38]), "+f"(d[39]), "+f"(d[40]), "+f"(d[41]), "+f"(d[42]), "+f"(d[43]), "+f"(d[44]), "+f"(d[45]), "+f"(d[46]), "+f"(d[47]), "+f"(d[48]), "+f"(d[49]), "+f"(d[50]), "+f"(d[51]), "+f"(d[52]), "+f"(d[53]), "+f"(d[54]), "+f"(d[55]), "+f"(d[56]), "+f"(d[57]), "+f"(d[58]), "+f"(d[59]), "+f"(d[60]), "+f"(d[61]), "+f"(d[62]), "+f"(d[63]), "+f"(d[64]), "+f"(d[65]), "+f"(d[66]), "+f"(d[67]), "+f"(d[68]), "+f"(d[69]), "+f"(d[70]), "+f"(d[71]), "+f"(d[72]), "+f"(d[73]), "+f"(d[74]), "+f"(d[75]), "+f"(d[76]), "+f"(d[77]), "+f"(d[78]), "+f"(d[79]), "+f"(d[80]), "+f"(d[81]), "+f"(d[82]), "+f"(d[83]), "+f"(d[84]), "+f"(d[85]), "+f"(d[86]), "+f"(d[87]), "+f"(d[88]), "+f"(d[89]), "+f"(d[90]), "+f"(d[91]), "+f"(d[92]), "+f"(d[93]), "+f"(d[94]), "+f"(d[95])
    : "l"(da), "l"(db), "r"(scale_d));
}

__device__ __forceinline__ void wgmma_n48_ss_ta0_tb1(float (&d)[24], uint64_t da, uint64_t db, int scale_d) {
  asm volatile("{\n.reg .pred p;\nsetp.ne.b32 p, %26, 0;\n"
    "wgmma.mma_async.sync.aligned.m64n48k16.f32.bf16.bf16 "
    "{%0, %1, %2, %3, %4, %5, %6, %7, %8, %9, %10, %11, %12, %13, %14, %15, "
    "%16, %17, %18, %19, %20, %21, %22, %23}, "
    "%24, %25, p, 1, 1, 0, 1;\n}\n"
    : "+f"(d[0]), "+f"(d[1]), "+f"(d[2]), "+f"(d[3]), "+f"(d[4]), "+f"(d[5]), "+f"(d[6]), "+f"(d[7]), "+f"(d[8]), "+f"(d[9]), "+f"(d[10]), "+f"(d[11]), "+f"(d[12]), "+f"(d[13]), "+f"(d[14]), "+f"(d[15]), "+f"(d[16]), "+f"(d[17]), "+f"(d[18]), "+f"(d[19]), "+f"(d[20]), "+f"(d[21]), "+f"(d[22]), "+f"(d[23])
    : "l"(da), "l"(db), "r"(scale_d));
}

__device__ __forceinline__ void wgmma_n192_rs_ta0_tb1(float (&d)[96], uint32_t a0, uint32_t a1, uint32_t a2, uint32_t a3, uint64_t db, int scale_d) {
  asm volatile("{\n.reg .pred p;\nsetp.ne.b32 p, %101, 0;\n"
    "wgmma.mma_async.sync.aligned.m64n192k16.f32.bf16.bf16 "
    "{%0, %1, %2, %3, %4, %5, %6, %7, %8, %9, %10, %11, %12, %13, %14, %15, "
    "%16, %17, %18, %19, %20, %21, %22, %23, %24, %25, %26, %27, %28, %29, %30, %31, "
    "%32, %33, %34, %35, %36, %37, %38, %39, %40, %41, %42, %43, %44, %45, %46, %47, "
    "%48, %49, %50, %51, %52, %53, %54, %55, %56, %57, %58, %59, %60, %61, %62, %63, "
    "%64, %65, %66, %67, %68, %69, %70, %71, %72, %73, %74, %75, %76, %77, %78, %79, "
    "%80, %81, %82, %83, %84, %85, %86, %87, %88, %89, %90, %91, %92, %93, %94, %95}, "
    "{%96, %97, %98, %99}, %100, p, 1, 1, 1;\n}\n"
    : "+f"(d[0]), "+f"(d[1]), "+f"(d[2]), "+f"(d[3]), "+f"(d[4]), "+f"(d[5]), "+f"(d[6]), "+f"(d[7]), "+f"(d[8]), "+f"(d[9]), "+f"(d[10]), "+f"(d[11]), "+f"(d[12]), "+f"(d[13]), "+f"(d[14]), "+f"(d[15]), "+f"(d[16]), "+f"(d[17]), "+f"(d[18]), "+f"(d[19]), "+f"(d[20]), "+f"(d[21]), "+f"(d[22]), "+f"(d[23]), "+f"(d[24]), "+f"(d[25]), "+f"(d[26]), "+f"(d[27]), "+f"(d[28]), "+f"(d[29]), "+f"(d[30]), "+f"(d[31]), "+f"(d[32]), "+f"(d[33]), "+f"(d[34]), "+f"(d[35]), "+f"(d[36]), "+f"(d[37]), "+f"(d[38]), "+f"(d[39]), "+f"(d[40]), "+f"(d[41]), "+f"(d[42]), "+f"(d[43]), "+f"(d[44]), "+f"(d[45]), "+f"(d[46]), "+f"(d[47]), "+f"(d[48]), "+f"(d[49]), "+f"(d[50]), "+f"(d[51]), "+f"(d[52]), "+f"(d[53]), "+f"(d[54]), "+f"(d[55]), "+f"(d[56]), "+f"(d[57]), "+f"(d[58]), "+f"(d[59]), "+f"(d[60]), "+f"(d[61]), "+f"(d[62]), "+f"(d[63]), "+f"(d[64]), "+f"(d[65]), "+f"(d[66]), "+f"(d[67]), "+f"(d[68]), "+f"(d[69]), "+f"(d[70]), "+f"(d[71]), "+f"(d[72]), "+f"(d[73]), "+f"(d[74]), "+f"(d[75]), "+f"(d[76]), "+f"(d[77]), "+f"(d[78]), "+f"(d[79]), "+f"(d[80]), "+f"(d[81]), "+f"(d[82]), "+f"(d[83]), "+f"(d[84]), "+f"(d[85]), "+f"(d[86]), "+f"(d[87]), "+f"(d[88]), "+f"(d[89]), "+f"(d[90]), "+f"(d[91]), "+f"(d[92]), "+f"(d[93]), "+f"(d[94]), "+f"(d[95])
    : "r"(a0), "r"(a1), "r"(a2), "r"(a3), "l"(db), "r"(scale_d));
}

__device__ __forceinline__ void wgmma_n48_rs_ta0_tb1(float (&d)[24], uint32_t a0, uint32_t a1, uint32_t a2, uint32_t a3, uint64_t db, int scale_d) {
  asm volatile("{\n.reg .pred p;\nsetp.ne.b32 p, %29, 0;\n"
    "wgmma.mma_async.sync.aligned.m64n48k16.f32.bf16.bf16 "
    "{%0, %1, %2, %3, %4, %5, %6, %7, %8, %9, %10, %11, %12, %13, %14, %15, "
    "%16, %17, %18, %19, %20, %21, %22, %23}, "
    "{%24, %25, %26, %27}, %28, p, 1, 1, 1;\n}\n"
    : "+f"(d[0]), "+f"(d[1]), "+f"(d[2]), "+f"(d[3]), "+f"(d[4]), "+f"(d[5]), "+f"(d[6]), "+f"(d[7]), "+f"(d[8]), "+f"(d[9]), "+f"(d[10]), "+f"(d[11]), "+f"(d[12]), "+f"(d[13]), "+f"(d[14]), "+f"(d[15]), "+f"(d[16]), "+f"(d[17]), "+f"(d[18]), "+f"(d[19]), "+f"(d[20]), "+f"(d[21]), "+f"(d[22]), "+f"(d[23])
    : "r"(a0), "r"(a1), "r"(a2), "r"(a3), "l"(db), "r"(scale_d));
}

__device__ __forceinline__ void wgmma_n80_rs_ta0_tb1(float (&d)[40], uint32_t a0, uint32_t a1, uint32_t a2, uint32_t a3, uint64_t db, int scale_d) {
  asm volatile("{\n.reg .pred p;\nsetp.ne.b32 p, %45, 0;\n"
    "wgmma.mma_async.sync.aligned.m64n80k16.f32.bf16.bf16 "
    "{%0, %1, %2, %3, %4, %5, %6, %7, %8, %9, %10, %11, %12, %13, %14, %15, "
    "%16, %17, %18, %19, %20, %21, %22, %23, %24, %25, %26, %27, %28, %29, %30, %31, "
    "%32, %33, %34, %35, %36, %37, %38, %39}, "
    "{%40, %41, %42, %43}, %44, p, 1, 1, 1;\n}\n"
    : "+f"(d[0]), "+f"(d[1]), "+f"(d[2]), "+f"(d[3]), "+f"(d[4]), "+f"(d[5]), "+f"(d[6]), "+f"(d[7]), "+f"(d[8]), "+f"(d[9]), "+f"(d[10]), "+f"(d[11]), "+f"(d[12]), "+f"(d[13]), "+f"(d[14]), "+f"(d[15]), "+f"(d[16]), "+f"(d[17]), "+f"(d[18]), "+f"(d[19]), "+f"(d[20]), "+f"(d[21]), "+f"(d[22]), "+f"(d[23]), "+f"(d[24]), "+f"(d[25]), "+f"(d[26]), "+f"(d[27]), "+f"(d[28]), "+f"(d[29]), "+f"(d[30]), "+f"(d[31]), "+f"(d[32]), "+f"(d[33]), "+f"(d[34]), "+f"(d[35]), "+f"(d[36]), "+f"(d[37]), "+f"(d[38]), "+f"(d[39])
    : "r"(a0), "r"(a1), "r"(a2), "r"(a3), "l"(db), "r"(scale_d));
}

template <bool kUseSmid>
__global__ void __cluster_dims__(2, 1, 1) __launch_bounds__(384, 1) fused_block_kernel(const uint8_t* __restrict__ gx, const uint8_t* __restrict__ gw, uint64_t gd, const __grid_constant__ Params P) {
  extern __shared__ __align__(1024) uint8_t smem_raw[];
  const uint32_t c_entry = (uint32_t)clock64();
  const uint32_t tid = threadIdx.x;
  uint32_t id = blockIdx.x;
  if (kUseSmid) asm volatile("mov.u32 %0, %%smid;" : "=r"(id));
  uint64_t p0;
  {
    const uint32_t isw = tid & 128, t = (tid >> 3 & 12) | (tid & 3);
    const uint64_t m = (uint64_t)((int64_t)((uint64_t)tid << 56) >> 63);
    p0 = reinterpret_cast<uint64_t>(gx) + (gd & m) + ((id & 127) * (isw ? 15 * 128 : 16 * 1280) + t * (isw ? 128 : 1280));
    asm volatile("{\n.reg .pred p;\nsetp.lt.u32 p, %1, 256;\n@p prefetch.global.L2 [%0];\n}" ::"l"(p0), "r"(tid));
  }
  const uint32_t sw = __shfl_sync(0xffffffffu, smem_u32(smem_raw) + (id << 12) + (tid >> 5), 0);
  const uint32_t sb = kUseSmid ? sw & 0xFF000400u : smem_u32(smem_raw), warp = sw & 31;
  if (kUseSmid) id = (sw >> 12) & 255;
#define BAR(i) (sb + kBars + 8 * (i))
  if (warp >= 8 && elect()) {
    const uint32_t cnt = (0x1381u >> (4 * warp - 32)) & 15;
#pragma unroll
    for (int i = 0; i < 4; i++) mbar_init(BAR(4 * (warp - 8) + i), cnt);
    asm volatile("fence.mbarrier_init.release.cluster;" ::: "memory");
  }
  asm volatile("barrier.cluster.arrive.relaxed.aligned;" ::: "memory");
  if (warp != 8) {
    if (warp - 1 < 3 && elect()) asm volatile("prefetch.tensormap [%0];" ::"l"(&P.mx + (warp - 1)) : "memory");
    asm volatile("barrier.cluster.wait.aligned;" ::: "memory");
    if (warp < 8) {
#pragma unroll 1
      for (uint32_t i = 0; i < X_PFC; i++) {
        spin_until(c_entry + X_PF1 + i * X_PFD);
        p0 += warp & 4 ? 1920 * 128 : 128;
        asm volatile("prefetch.global.L2 [%0];" ::"l"(p0));
      }
    }
  }
  const uint32_t lane = __shfl_sync(0xffffffffu, tid & 31, tid & 31);
  const uint32_t tp = id >> 1, par = kUseSmid ? sw >> 24 : id & 1;
  uint32_t beta = tp & 7, idx = tp >> 3;
  if (tp >= 32) { const uint32_t u = tp - 32, d = (u * 37) >> 8, r = u - 7 * d; beta = d < 4 ? 1 + r : 0; idx = d < 4 ? 4 + d : 2 + r; }
  if ((tp >> 1) == 30) {
    const uint32_t h = (id - 120) * 384 + tid;
    uint4* z = P.scr + offsetof(Scratch, stat1) / 16 + h;
#pragma unroll 1
    for (uint32_t n = 0; n < kReset; n++) {
      if (n == 1) { __syncthreads(); spin_until(c_entry + X_ZAT); }
      z[n * 1536] = make_uint4(0, 0, 0, 0);
      if (n == 0 || n == kReset1 - 1 || n == kReset2 - 1 || n == kReset - 1) {
        __syncthreads();
        if (tid == 0) asm volatile("red.release.gpu.global.add.u32 [%0], 1;" ::"l"(P.count + (n / 12 + 1) * 32) : "memory");
      }
      if (n - kReset1 < 5 && h < 1280) asm volatile("prefetch.global.L2 [%0];" ::"l"(P.wo + ((n - kReset1) * 1280 + h) * 128));
    }
    return;
  }
  const uint32_t rb = beta, hg = idx;
  auto half_stage = [&](uint32_t kb, uint32_t h) {
    const uint32_t s = sb + ((kb + 2) & 3) * kStage, fb = BAR((h ? B_FULL : B_HALF) + (kb & 3)), ks = 2 * h + par;
    mbar_expect_tx(fb, kStage / 2);
    tma_3d_mc(s + 16384 + ks * 6144, &P.mw64, fb, 80 * hg, kb * 64 + 16 * ks, 0);
    tma_3d_mc(s + 40960 + ks * 1536, &P.mw16, fb, 80 * hg + 64, kb * 64 + 16 * ks, 0);
    tma_2d(s + 8192 - h * 8192, &P.mx, fb, par * 640 + kb * 64, rb * 128 + 64 - h * 64);
  };
  if (warp == 8) {
    asm volatile("barrier.cluster.wait.aligned;" ::: "memory");
    PROF(1);
    if (elect()) { half_stage(0, 0); half_stage(0, 1); }
  }
  const uint32_t tile = 2 * rb + par, cta = tile * 8 + hg;
  const uint64_t fm = 0xF7F777777777770Full >> (rb * 8 + hg);
  const uint32_t fi = fm & 1 ? 2 * __popcll(fm) - 2 + par : 96;
#define UNIT(field, i) (at(P.scr, i) + offsetof(Scratch, field) / 16)
#define WORD(field, i) (at(reinterpret_cast<uint32_t*>(P.scr), i) + offsetof(Scratch, field) / 4)

  const uint32_t g = lane >> 2, q = lane & 3, m = lane >> 3, l7 = lane & 7;
  int spin = kSpin;

  if (warp >= 8) {
    asm volatile("setmaxnreg.dec.sync.aligned.u32 56;");
    auto permute = [&]() {
      mbar_wait(BAR(B_TAIL), 0);
      PROF(31);
      const uint32_t a = sb + kWoTail + lane * 16, x = (2 * (hg & 3) ^ m) << 4;
#pragma unroll 1
      for (int i = 0; i < 20480; i += 512 * X_PB) {
        uint4 v[X_PB];
#pragma unroll
        for (int e = 0; e < X_PB; e++) v[e] = lds16(a + i + e * 512);
        __syncwarp();
#pragma unroll
        for (int e = 0; e < X_PB; e++) sts16((a ^ x ^ (e & 1) * 64) + i + e * 512, v[e].x, v[e].y, v[e].z, v[e].w);
      }
      fence_async();
      __syncwarp();
      PROF(21);
    };
    auto wait_reset = [&](int i, uint32_t e) {
      unsigned c;
#pragma unroll 1
      do {
        asm volatile("ld.acquire.gpu.global.u32 %0, [%1];" : "=r"(c) : "l"(P.count + i) : "memory");
      } while (c != 4 * e && --spin > 0);
    };
    if (warp == 8) {
      const uint8_t* pf = (lane < 16 ? gx : gw) + (lane < 16 ? (cta * 16 + lane) * 10 + X_PFC : cta * 15 + min(lane, 30u) - 16 + X_PFC * 1920) * 128;
      auto prefetch = [&]() { pf += lane < 16 ? 128 : 1920 * 128; asm volatile("prefetch.global.L2 [%0];" ::"l"(pf)); };
#pragma unroll 1
      for (uint32_t kb = 1; kb < 10; kb++) {
        spin_until(c_entry + X_GAP0 + kb * X_GAP);
        if (kb >= 4) mbar_wait(BAR(B_EMPTY + (kb & 3)), kb >> 3);
        if (elect()) { half_stage(kb, 0); half_stage(kb, 1); }
        if (kb == 10 - kNs) bar_sync(NB_RED, 64);
        if (kb >= 5 && fi < 96 && elect()) {
          const uint32_t n = kb - 5;
          tma_2d(sb + kGate + n * 4096, &P.mgate, BAR(B_FFN), 16 * (fi & ~1u), n < 4 ? 256 * par + 64 * n : 512 + 64 * par);
        }
        if (kb < 10 - X_PFC - kNs) prefetch();
      }
      const uint32_t fc = 16 * (fi & ~1u);
      const bool ffn = fi < 96 && elect();
      if (ffn) {
        mbar_expect_tx(BAR(B_FFN), 61440);
        asm volatile("mbarrier.arrive.shared::cta.b64 _, [%0], 2;" ::"r"(BAR(B_FFN)) : "memory");
      }
#pragma unroll 1
      for (uint32_t n = 0; n < 4; n++) {
        mbar_wait(BAR(B_EMPTY + 2 + (n >= 2)), 1);
        const uint32_t t = (uint32_t)clock64(), i = 2 * n + par;
        if (elect()) tma_2d_mc(sb + kWo + i * 10240, &P.mwo, BAR(B_WO), 64 * hg, 80 * (hg ^ i));
        spin_until(t + X_WGAP);
      }
      if (ffn) mbar_expect_tx(BAR(B_FULL + 2), 1024);
      PROF(20);
      bar_sync(NB_OL, 288);
      uint32_t t = clock_ordered();
#pragma unroll 1
      for (uint32_t n = 0; n < 5; n++) {
        spin_until(t);
        if (fi < 96 && elect()) tma_2d(sb + kUp + n * 4096, &P.mup, BAR(B_FFN), fc, n < 4 ? 256 * par + 64 * n : 512 + 64 * par);
        spin_until(t + X_GGAP2);
        if (fi < 96 && elect()) tma_3d(sb + kDown + n * 4096, &P.mdown, BAR(B_FFN), 0, fc + 16 * par, 2 * n);
        t += 2 * X_GGAP2;
      }
      PROF(60);
      const uint2 et = lds8(sb + kMisc);
      const uint32_t* kp = WORD(keys, 2 * (lane & 15));
      const uint32_t cu = par * 48 + (g & 3) * 12 + q;
      uint32_t k, kt, tn;
      mbar_wait(BAR(B_HALF + 2), 0);
      spin_until((uint32_t)clock64() + X_LWAIT);
#pragma unroll 1
      do { tn = __reduce_max_sync(0xffffffffu, ld_word(WORD(last, lane & 15)) - 1) + 1; } while (!tn && --spin > 0);
      PROF(55);
      tn += X_KNS;
      until_ns(tn);
#pragma unroll 1
      do {
        asm volatile("{\n.reg .b64 t;\nld.relaxed.gpu.global.b64 t, [%2];\nmov.b64 {%0, %1}, t;\n}" : "=r"(k), "=r"(kt) : "l"(kp) : "memory");
        k = __reduce_max_sync(0xffffffffu, k - 1) + 1;
      } while (!k && --spin > 0);
      PROF(14);
      const uint4* p = UNIT(cand, ((~k >> 4 & 0x70) + (~k & 1) * 8 + (~k >> 5 & 7)) * 96 + cu);
      bool ok;
#pragma unroll 1
      do {
        if (fi >= 96) { stsf(sb + kMisc + 8, __uint_as_float(k)); break; }
        const uint4 v0 = ld_msg(p), v1 = ld_msg(p + 4), v2 = ld_msg(p + 8);
        sts8(sb + kMisc + 8, k, max(tn, __reduce_max_sync(0xffffffffu, kt) + X_KT));
        sts16(sb + kSel + lane * 48, __byte_perm(v0.x, v2.z, 0x3254), v0.y, v0.z, v0.w);
        sts16(sb + kSel + lane * 48 + 16, __byte_perm(v1.x, v2.z, 0x3276), v1.y, v1.z, v1.w);
        sts8(sb + kSel + lane * 48 + 32, v2.x, v2.y);
        ok = all(!(lop3<0xF6>(lop3<0x7E>(v0.x, v1.x, et.y), v2.w, et.y) & 1));
      } while (!ok && --spin > 0);
      bar_arrive(NB_KEY + 1, 320);
      PROF(15);
      st_word_if(lane + cta == 0, P.count, et.x);
      return;
    }
    const bool sd = warp == 11;
    uint32_t e;
    const uint32_t u = min(tile, 14u);
    if (sd) {
      const uint8_t* sx = gx + (256 * rb + par + 32 * hg + 2 * m) * 1280 + (10 - kNs) * 128 + l7 * 16;
      const uint8_t* sv = gw + (640 - 64 * kNs + (lane >> 1)) * 3840 + (u < 12 ? (u >> 2) * 1280 + (u & 3) * 32 : u * 1280 - 12 * 1280 + 128) + 160 * hg + (lane & 1) * 16;
      e = ld_word(P.count) + 1;
      spin_until(c_entry + X_SAT);
#pragma unroll 1
      for (uint32_t i = 0; i < 4 * kNs; i++) {
        asm volatile("cp.async.cg.shared.global [%0], [%1], 16;" ::"r"(sb + kUpSide + i * 512 + m * 128 + ((l7 ^ m ^ (i & 1) * 4) << 4)), "l"(sx + (i & 3) * 10240 + (i >> 2) * 128) : "memory");
        asm volatile("cp.async.cg.shared.global [%0], [%1], 16;" ::"r"(sb + kUpSide + 2048 * kNs + i * 512 + ((lane ^ (lane >> 3 & 1)) << 4)), "l"(sv + i * (16 * 3840)) : "memory");
      }
      wait_reset(32, e);
      asm volatile("cp.async.wait_all;" ::: "memory");
      __syncwarp();
    }
    bool cw = warp == 10;
    float s0, s1, q0, q1;
#pragma unroll 1
    while (true) {
      uint32_t o0 = ((sd ? 0 : 16 * hg) + (lane & 15)) * 128 + (((m >> 1) ^ l7) << 4), o1 = o0 ^ 32, o2 = o0 ^ 64, o3 = o0 ^ 96;
      if (cw) {
        const bool wide = u < 12 && !sd;
        const uint32_t k = 8 * (m >> 1) + l7, st = wide ? 6144 : sd ? 512 : 1536;
        o0 = wide ? 16384 + (u >> 2) * 2048 + k * 128 + (((2 * (u & 3) + (m & 1)) ^ l7) << 4) : (sd ? 2048 * kNs : 34816 + u * 512) + k * 32 + (((m & 1) ^ (l7 >> 2)) << 4);
        o1 = o0 + st; o2 = o1 + st; o3 = o2 + st;
      }
      s0 = s1 = q0 = q1 = 0.f;
#pragma unroll 1
      for (uint32_t kb = sd ? 10 - 2 * kNs : 0; kb < 10 - kNs; kb++) {
        if (!sd) {
          if (kb == 9 - kNs) {
            bar_sync(NB_GRID, 96);
            const uint4 p = lds16(sb + (cw ? kBext : kStat) + lane * 16);
            s0 += __uint_as_float(p.x); s1 += __uint_as_float(p.y); q0 += __uint_as_float(p.z); q1 += __uint_as_float(p.w);
          }
          mbar_wait(BAR(B_HALF + (kb & 3)), kb >> 2);
          mbar_wait(BAR(B_FULL + (kb & 3)), kb >> 2);
          if (warp == 9) PROF2(47, kb);
        }
        const uint32_t s = sb + (sd ? kUpSide - (10 - 2 * kNs) * 2048 + kb * 2048 : ((kb + 2) & 3) * kStage), a0 = s + o0, a1 = s + o1, a2 = s + o2, a3 = s + o3;
        uint32_t r[16];
        if (cw) { ldsm4t(r[0], r[1], r[2], r[3], a0); ldsm4t(r[4], r[5], r[6], r[7], a1); ldsm4t(r[8], r[9], r[10], r[11], a2); ldsm4t(r[12], r[13], r[14], r[15], a3); }
        else { ldsm4(r[0], r[1], r[2], r[3], a0); ldsm4(r[4], r[5], r[6], r[7], a1); ldsm4(r[8], r[9], r[10], r[11], a2); ldsm4(r[12], r[13], r[14], r[15], a3); }
#pragma unroll
        for (int i = 0; i < 16; i += 2) {
          const float a = bf_lo(r[i]), b = bf_hi(r[i]), c = bf_lo(r[i + 1]), d = bf_hi(r[i + 1]);
          s0 += a; s0 += b; q0 = fmaf(a, a, q0); q0 = fmaf(b, b, q0);
          s1 += c; s1 += d; q1 = fmaf(c, c, q1); q1 = fmaf(d, d, q1);
        }
        if (lane < 2 && !sd) mbar_arrive_cta(BAR(B_EMPTY + (kb & 3)) + (__float_as_uint(q0) >> 31), lane);
      }
      if (!sd) break;
      sts16(sb + (cw ? kBext : kStat) + lane * 16, __float_as_uint(s0), __float_as_uint(s1), __float_as_uint(q0), __float_as_uint(q1));
      if (cw) break;
      cw = true;
    }
    if (warp == 11) {
      PROF(56);
      bar_arrive(NB_GRID, 96);
      bar_arrive(NB_RED, 64);
      if (elect()) {
        mbar_expect_tx(BAR(B_TAIL), 20480);
        asm volatile("mbarrier.arrive.shared::cta.b64 _, [%0], 2;" ::"r"(BAR(B_TAIL)) : "memory");
      }
      if (elect()) {
#pragma unroll 1
        for (int i = 0; i < 5; i++) asm volatile("prefetch.tensormap [%0];" ::"l"(&P.mwo + i) : "memory");
      }
      __syncwarp();
      wait_reset(64, e);
      sts8(sb + kMisc, e, e & 1);
      if (elect()) mbar_arrive(BAR(B_AUX));
      PROF(22);
      sleep_until(c_entry + X_TAT);
      if (elect()) {
#pragma unroll 1
        for (uint32_t n = 0; n < 4; n++) {
          const uint32_t t = (uint32_t)clock64() + X_TGAP;
          tma_3d_mc(sb + kWoTail + par * 10240 + n * 2560, &P.mtail, BAR(B_TAIL), 512 + 16 * hg, (hg & 4) ^ (4 * par), 20 * n);
          spin_until(t);
        }
      }
      __syncwarp();
      permute();
      if (elect()) asm volatile("mbarrier.arrive.shared::cta.b64 _, [%0], 2;" ::"r"(BAR(B_WO)) : "memory");
      {
        const uint32_t w0 = __ldg(at(P.wr, 32 * hg + lane)), w1 = g < 2 ? __ldg(at(P.wr, 8 * hg + lane) + 256) : 0u;
        float s = (bf_lo(w0) + bf_hi(w0)) + (bf_lo(w1) + bf_hi(w1));
#pragma unroll 1
        for (int o = 16; o >= 1; o >>= 1) s += shx(s, o);
        stsf(sb + kWr + q * 48 + g * 4, __uint_as_float(w0));
        stsf(sb + kWr + q * 48 + 32 + min(g, 2u) * 4, g < 2 ? __uint_as_float(w1) : __uint_as_float(nz(__float_as_uint(s))));
        __syncwarp();
      }
      wait_reset(96, e);
      PROF(30);
      if (elect()) asm volatile("mbarrier.arrive.shared::cta.b64 _, [%0], 3;" ::"r"(BAR(B_TAIL)) : "memory");
    } else {
      PROF2(23, cw);
      s0 = (q & 1 ? s1 : s0) + shx(q & 1 ? s0 : s1, 1); q0 = (q & 1 ? q1 : q0) + shx(q & 1 ? q0 : q1, 1);
      s0 += shx(s0, 2); q0 += shx(q0, 2);
      s0 *= cw ? 1.f : -1.f / 640;
      uint32_t w = pack_bf16(s0, s0 - bf_round(s0));
      const float r = bf_round(sqr(bf_round(bf_round(fmaxf(fmaf(q0, 1.f / 640, -s0 * s0), 0.f)) + 1e-5f)));
      if (cw) asm volatile("movmatrix.sync.aligned.m8n8.trans.b16 %0, %0;" : "+r"(w));
      else if (q & 2) w = __float_as_uint(r);
      const uint32_t src = cw ? (uint32_t)(offsetof(Scratch, cs) / 16) + hg * 64 : (uint32_t)(offsetof(Scratch, stat1) / 16) - 8 + (par * 8 + rb) * 64;
      st_word_if(!cw || lane < 16, WORD(obuf, 4 * src + (cw ? 16 * u : 32 + 32 * hg) + lane), nz(w));
      PROF2(57, cw);
      {
        const uint32_t i0 = (cw || rb) ? lane : max(lane, 8u), i1 = min(lane + 32, cw ? 59u : 63u), i2 = cw ? 59 : 64 + l7;
        uint4 v0, v1, v2;
        spin_until((uint32_t)clock64() + X_AWAIT);
#pragma unroll 1
        do {
          v0 = ld_words(UNIT(obuf, src + i0)); v1 = ld_words(UNIT(obuf, src + i1)); v2 = ld_words(UNIT(obuf, src + i2));
        } while (!all(min(min(min(min(v0.x, v0.y), min(v0.z, v0.w)), min(min(v1.x, v1.y), min(v1.z, v1.w))), min(min(v2.x, v2.y), min(v2.z, v2.w)))) && --spin > 0);
        const uint32_t d = sb + (cw ? kBext : kStat);
        sts16(d + lane * 16, v0.x, v0.y, v0.z, v0.w); sts16(d + 512 + lane * 16, v1.x, v1.y, v1.z, v1.w); sts16(d + 1024 + l7 * 16, v2.x, v2.y, v2.z, v2.w);
      }
      fence_async();
      __syncwarp();
      PROF2(25, cw);
      mbar_wait(BAR(B_FULL + 1), 0);
      if (elect()) mbar_arrive(BAR(B_AUX));
      if (lane < 2) mbar_arrive_cta(BAR(B_EMPTY + 1), lane);
      auto note = [&](int i, uint32_t wait) {
        uint32_t* const hp = WORD(hint, tile * 32 + l7) + 512 * i;
        const uint32_t c = clock_ordered();
        st_word_if(lane == hg, hp, nz(now_ns()));
        spin_until(c + wait);
        uint32_t t;
#pragma unroll 1
        do { t = __reduce_max_sync(0xffffffffu, ld_word(hp) - 1) + 1; } while (!t && --spin > 0);
        return t;
      };
      if (!cw) {
        uint4 v[5];
#pragma unroll
        for (int i = 0; i < 5; i++) v[i] = make_uint4(0, 0, 0, 0);
        mbar_wait(BAR(B_AUX), 0);
        mbar_wait(BAR(B_EMPTY + 3), 1);
        if (rb) {
#pragma unroll 1
          while (!ld_word(UNIT(soon, cta * 8)) && --spin > 0) {}
          spin_until((uint32_t)clock64() + X_SOON);
#pragma unroll 1
          do {
            PROF(5);
#pragma unroll
            for (int i = 0; i < 5; i++) v[i] = ld_msg(UNIT(halo, cta * 160 + lane) + (32 * i - 2560));
          } while (!all(min(min(v[0].x, v[1].x), min(min(v[2].x, v[3].x), v[4].x))) && --spin > 0);
        }
        sts16(sb + kKst + lane * 16, v[0].x, v[0].y, v[0].z, v[0].w);
        sts16(sb + kKst + 512 + lane * 16, v[1].x, v[1].y, v[1].z, v[1].w);
        sts8(sb + kKst + 1024 + lane * 8, v[2].x, v[2].y);
        const uint32_t a = sb + kVst + l7 * kPitch + m * 16;
        stsm4(a, v[3].x, v[3].y, v[3].z, v[3].w);
        stsm4(a + 64, v[4].x, v[4].y, v[4].z, v[4].w);
        stsm2(a + 128, v[2].z, v[2].w);
        bar_arrive(NB_KV, 64);
        PROF(27);
        uint32_t* kp = WORD(keys, 2 * tile);
        mbar_wait(BAR(B_EMPTY + 1), 0);
        bar_sync(NB_KEY, 288);
        const uint32_t tn = now_ns();
        const uint4 ka = lds16(sb + kMisc + 16), kb = lds16(sb + kMisc + 32);
        asm volatile("{\n.reg .pred p;\n.reg .b64 t;\nsetp.eq.u32 p, %3, 0;\nmov.b64 t, {%1, %2};\n@p st.relaxed.gpu.global.b64 [%0], t;\n}"
                     ::"l"(kp), "r"(max(max(max(ka.x, ka.y), max(ka.z, ka.w)), max(max(kb.x, kb.y), max(kb.z, kb.w)))), "r"(tn), "r"(lane + hg) : "memory");
        PROF(13);
        wait_reset(128, __float_as_uint(ldsf(sb + kMisc)));
        PROF(6);
        bar_arrive(NB_KEY + 1, 320);
        return;
      }
      mbar_wait(BAR(B_EMPTY + 1), 0);
      const uint32_t tg = note(0, X_HWAIT) + X_GNS;
      until_ns(tg);
      PROF(29);
      if (elect()) mbar_expect_tx(BAR(B_WO), 81920);
      mbar_wait(BAR(B_WO), 0);
      until_ns((tg + X_WD));
      if (elect()) mbar_arrive(BAR(B_FULL + 3));
      bar_sync(NB_RED, 64);
      const uint32_t tl = note(1, X_NWAIT);
      stsf(sb + kMisc + 12, __uint_as_float(tl));
      st_word_if(lane + hg == 0, WORD(last, tile), tl);
      if (elect()) mbar_arrive(BAR(B_HALF + 2));
      PROF(53);
    }
    bar_sync(warp & 1 ? 0 : NB_GRID, 160);
#pragma unroll 1
    for (uint32_t w = 4 * (warp & 1); w < 4 * (warp & 1) + 4; w++) {
      const uint32_t ao = sb + kOutSt + w * (16 * kPitch), crow = __float_as_uint(ldsf(ao + 160));
      uint4* po = at(reinterpret_cast<uint4*>(P.out), (256 * rb + par + 32 * w) * 80);
#pragma unroll
      for (int i = 0; i < 5; i++) {
        const uint32_t row = i < 4 ? 4 * i + m : lane >> 1, ch = i < 4 ? l7 : 8 + (lane & 1);
        const uint4 v = lds16(ao + row * kPitch + ch * 16);
        if (row != crow) *at(po, row * 160 + (i < 4 ? 8 * hg : 56 + 2 * hg) + ch) = v;
      }
    }
    PROF(59);
  } else {
    asm volatile("setmaxnreg.inc.sync.aligned.u32 224;");
    const uint32_t wg = warp >> 2;
    const uint32_t s16 = kUseSmid ? 64u : (sb & 0x3FFFF) >> 4;
    const bool gt0 = 2 * q > g, gt1 = 2 * q + 1 > g;
    const bool rel = lane + 8 * (warp & 3) < 2;
    float acc1[96], acc2[24];
    const uint32_t ax = sb + (16 * warp + (lane & 15)) * 128 + (((lane >> 4) ^ l7) << 4);
    uint32_t xr[10][2];
    auto wide = [&](uint32_t so, int k, int acc_on) { wgmma_n192_ss_ta0_tb1(acc1, make_desc(s16 + (so >> 4) + wg * 512 + 2 * k, 16, 1024, 1), make_desc(s16 + (so >> 4) + 1024 + 384 * k, 2048, 1024, 1), acc_on); };
    auto slim = [&](uint32_t so, int k, int acc_on) { wgmma_n48_ss_ta0_tb1(acc2, make_desc(s16 + (so >> 4) + wg * 512 + 2 * k, 16, 1024, 1), make_desc(s16 + (so >> 4) + 2560 + 96 * k, 512, 256, 3), acc_on); };
#pragma unroll 1
    for (uint32_t kb = 0;; kb++) {
      const uint32_t so = ((kb + 2) & 3) * kStage;
      if (wg) {
        if (kb >= X_MID) mbar_wait(BAR(B_FULL + (kb & 3)), (kb >> 2) & 1);
        mbar_wait(BAR(B_HALF + (kb & 3)), (kb >> 2) & 1);
      }
      if (warp == 4) PROF2(32, kb);
      wgmma_wait<0>();
      if (rel && kb) mbar_arrive_cta(BAR(B_EMPTY + ((kb - 1) & 3)), lane);
      if (kb == 8) break;
      if (wg == 0 || kb) bar_sync(NB_TURN + wg, 256);
      wgmma_fence();
      wide(so, 0, kb); slim(so, 0, kb); slim(so, 1, 1); wide(so, 1, 1);
      if (wg && kb < X_MID) mbar_wait(BAR(B_FULL + (kb & 3)), (kb >> 2) & 1);
      wide(so, 2, 1); slim(so, 2, 1);
      bar_arrive(NB_TURN + 1 - wg, 256);
      wide(so, 3, 1); slim(so, 3, 1);
      wgmma_commit();
      if (kb == hg) {
#pragma unroll
        for (int i = 0; i < 4; i++) ldsm4(xr[2 * i][0], xr[2 * i][1], xr[2 * i + 1][0], xr[2 * i + 1][1], (ax + so) ^ (32 * i));
        bar_sync(NB_WG + wg, 128);
      }
    }
    auto cvt = [&](int sec, int c, int h) { const float* a = c < 8 ? &acc1[32 * sec + 4 * c + 2 * h] : &acc2[8 * sec + 4 * (c - 8) + 2 * h]; return pack_at(a[0], a[1]); };
    uint32_t tag;
    float fs[4], lb[4];
    uint32_t sg[3];
    const uint32_t sa = sb + kStat + 128 + warp * 128;
#pragma unroll 1
    for (uint32_t ph = wg; ph != wg + 2; ph++) {
      if (ph == 1) {
        if (wg) mbar_wait(BAR(B_HALF + 1), 0);
        bar_sync(NB_TURN + wg, 256);
        wgmma_fence();
#pragma unroll
        for (int k = 0; k < 4; k++) { wide(2 * kStage, k, 1); slim(2 * kStage, k, 1); }
        wide(3 * kStage, 0, 1); slim(3 * kStage, 0, 1); slim(3 * kStage, 1, 1); wide(3 * kStage, 1, 1);
        if (wg) mbar_wait(BAR(B_AUX), 0);
        const uint2 st = lds8(sa + g * 16);
        wide(3 * kStage, 2, 1); slim(3 * kStage, 2, 1); wide(3 * kStage, 3, 1); slim(3 * kStage, 3, 1);
        const uint32_t m0 = q ? 0u : st.x, m1 = q ? 0u : st.y;
        const uint32_t a0 = __byte_perm(m0, 0, 0x1010), a1 = __byte_perm(m1, 0, 0x1010), a2 = __byte_perm(m0, 0, 0x3232), a3 = __byte_perm(m1, 0, 0x3232);
        if (warp == 4) PROF(28);
        if (wg) bar_arrive(NB_TURN, 256);
        st_word_if(lane + (warp ^ 7) == 0, UNIT(soon, cta * 8) + 128, 1);
        wgmma_fence();
        wgmma_n192_rs_ta0_tb1(acc1, a0, a1, a2, a3, make_desc(s16 + kBext / 16, 0, 32, 0), 1);
        wgmma_n48_rs_ta0_tb1(acc2, a0, a1, a2, a3, make_desc(s16 + (kBext + 768) / 16, 0, 32, 0), 1);
        wgmma_commit();
        if (warp == 7 && rb < 7) {
          uint4* p = UNIT(halo, cta * 160 + lane);
          wgmma_wait<0>();
          st_msg(p, nz(cvt(1, 0, 1)), cvt(1, 1, 1), cvt(1, 3, 1), cvt(1, 4, 1));
          st_msg(p + 32, nz(cvt(1, 5, 1)), cvt(1, 6, 1), cvt(1, 8, 1), cvt(1, 9, 1));
          st_msg(p + 64, nz(cvt(1, 2, 1)), cvt(1, 7, 1), cvt(2, 8, 1), cvt(2, 9, 1));
          st_msg(p + 96, nz(cvt(2, 0, 1)), cvt(2, 1, 1), cvt(2, 2, 1), cvt(2, 3, 1));
          st_msg(p + 128, nz(cvt(2, 4, 1)), cvt(2, 5, 1), cvt(2, 6, 1), cvt(2, 7, 1));
          PROF(4);
        }
      } else {
        mbar_wait(wg ? BAR(B_EMPTY + 3) : BAR(B_AUX), wg);
        if (!wg) mbar_wait(BAR(B_FULL), 0);
        ldsm4(xr[8][0], xr[8][1], xr[9][0], xr[9][1], (ax + (2 + (hg >> 2)) * kStage) ^ (32 * (hg & 3)));
        const uint2 so = lds8(sa + g * 16 + 8), k0 = lds8(sa + q * 32 + 8), k1 = lds8(sa + q * 32 + 24);
        const float p0 = ldsf(sa + q * 32 - 116), p1 = ldsf(sa + q * 32 - 100);
        tag = __float_as_uint(ldsf(sb + kMisc + 4));
        sg[0] = __byte_perm(__float_as_uint(p0), __float_as_uint(p1), 0x7632); sg[1] = __byte_perm(k0.x, k1.x, 0x7632); sg[2] = __byte_perm(k0.y, k1.y, 0x7632);
        const float sk[4] = {gt0 ? p0 : __uint_as_float(k0.x), gt1 ? p1 : __uint_as_float(k1.x), __uint_as_float(gt0 ? k0.x : k0.y), __uint_as_float(gt1 ? k1.x : k1.y)};
        const float f0 = __uint_as_float(so.x) * (4.47213595499958f / 1.4426950408889634f), f1 = __uint_as_float(so.y) * (4.47213595499958f / 1.4426950408889634f);
#pragma unroll
        for (int i = 0; i < 4; i++) { fs[i] = rcp(sk[i] * (i < 2 ? f0 : f1)); lb[i] = -lg2(sk[i]); }
        if (rb + warp == 0) { if (gt0) lb[0] = -1e30f; if (gt1) lb[1] = -1e30f; }
      }
    }
    uint32_t ak = sb + kKst + warp * 1280 + lane * 16, ak1 = ak + 1024 - lane * 8, bandm = (gt0 ? 0xFFFFu : 0u) | (gt1 ? 0xFFFF0000u : 0u);
    const uint32_t av = sb + 2 * kStage + warp * 2048 + l7 * kPitch;
    uint32_t ac = av + m * 16, ae = av + (m == 3 ? kStage : m ? 0 : warp ? kStage - 2048 : kVst - 2 * kStage);
    const uint32_t tw = tile * 8 + warp, oo = tw * 1280 + hg * 32 + lane;
    uint4* op = UNIT(obuf, oo);
    float acc[40];
    {
#pragma unroll
      for (int c = 0; c < 10; c++) { acc[4 * c] = bf_lo(xr[c][0]); acc[4 * c + 1] = bf_hi(xr[c][0]); acc[4 * c + 2] = bf_lo(xr[c][1]); acc[4 * c + 3] = bf_hi(xr[c][1]); }
#pragma unroll
      for (int i = 0; i < 40; i++) pin(acc[i]);
      pin(ak); pin(ak1); pin(ac); pin(ae); pin(bandm); pin(op);
      spin_until(c_entry);
      if (__float_as_uint(fs[1]) == 0xFFFFFFFFu) return;
      wgmma_wait<0>();
      if (rel) mbar_arrive_cta(BAR(B_EMPTY + 1), lane);
    }
    if ((warp & 3) == 0) PROF2(2, wg);

    uint32_t qc[10][2], kl[10], kh[10];
    {
      uint32_t vh[10], vl[10];
#pragma unroll
      for (int c = 0; c < 10; c++) kh[c] = cvt(1, c, 1);
      if (warp < 7) {
        sts16(ak + 1280, kh[0], kh[1], kh[3], kh[4]);
        sts16(ak + 1280 + 512, kh[5], kh[6], kh[8], kh[9]);
        sts8(ak1 + 1280, kh[2], kh[7]);
      }
#pragma unroll
      for (int c = 0; c < 10; c++) vh[c] = cvt(2, c, 1);
      stsm4(ac + kStage, vh[0], vh[1], vh[2], vh[3]);
      stsm4(ac + kStage + 64, vh[4], vh[5], vh[6], vh[7]);
      stsm2(ac + kStage + 128, vh[8], vh[9]);
      if (warp < 7) bar_arrive(NB_KV + 1 + warp, 64);
#pragma unroll
      for (int c = 0; c < 10; c++) vl[c] = cvt(2, c, 0);
      stsm4(ac, vl[0], vl[1], vl[2], vl[3]);
      stsm4(ac + 64, vl[4], vl[5], vl[6], vl[7]);
      stsm2(ac + 128, vl[8], vl[9]);
#pragma unroll
      for (int c = 0; c < 10; c++) { qc[c][0] = cvt(0, c, 0); qc[c][1] = cvt(0, c, 1); kl[c] = cvt(1, c, 0); }
      if (__float_as_uint(fs[0]) == 0xFFFFFFFFu) return;
      if (warp == X_PW) PROF(54);
      if (X_ADW ? warp == 0 : !wg) spin_until((uint32_t)clock64() + X_AD3);
      bar_sync(NB_KV + warp, 64);
    }

    uint32_t ow[10][2];
    auto publish = [&](int s) { st_msg(op + 256 * s, ow[2 * s][0], ow[2 * s][1], ow[2 * s + 1][0], ow[2 * s + 1][1]); };
    {
      const uint2 k2 = lds8(ak1);
#pragma unroll
      for (int p = 0; p < 2; p++) {
        const uint4 u = lds16(ak + 512 * p);
        const uint32_t kp[5] = {u.x, u.y, p ? k2.y : k2.x, u.z, u.w};
        uint32_t vf[5][4];
#pragma unroll
        for (int c = 0; c < 5; c++) {
          ldsm4t(vf[c][0], vf[c][1], vf[c][2], vf[c][3], ae + 80 * p + 16 * c);
        }
        float s[2][4], mx[2][2];
#pragma unroll
        for (int h = 0; h < 2; h++) {
          const int ca = 5 * p + 3 * h, cm = 5 * p + 2;
          const uint32_t qm0 = (q < 2) == (h == 0) ? qc[cm][0] : 0u, qm1 = (q < 2) == (h == 0) ? qc[cm][1] : 0u;
          float S[3][4];
#pragma unroll
          for (int kt = 2; kt >= 0; kt--) {
            const uint32_t* kk = kt == 0 ? kp - 5 * p : kt == 1 ? kl : kh;
            S[kt][0] = S[kt][1] = S[kt][2] = S[kt][3] = 0.f;
            mma16(S[kt], qc[ca][0], qc[ca][1], qc[ca + 1][0], qc[ca + 1][1], kk[ca], kk[ca + 1]);
            mma8(S[kt], qm0, qm1, kk[cm]);
          }
          s[h][0] = fmaf(gt0 ? S[0][0] : S[1][0], fs[0], lb[0]); s[h][1] = fmaf(gt1 ? S[0][1] : S[1][1], fs[1], lb[1]);
          s[h][2] = fmaf(gt0 ? S[1][2] : S[2][2], fs[2], lb[2]); s[h][3] = fmaf(gt1 ? S[1][3] : S[2][3], fs[3], lb[3]);
          mx[h][0] = fmaxf(s[h][0], s[h][1]); mx[h][1] = fmaxf(s[h][2], s[h][3]);
        }
#pragma unroll
        for (int of = 1; of <= 2; of <<= 1) {
#pragma unroll
          for (int i = 0; i < 4; i++) mx[i >> 1][i & 1] = fmaxf(mx[i >> 1][i & 1], shx(mx[i >> 1][i & 1], of));
        }
#pragma unroll
        for (int r = 1; r >= 0; r--) {
          const uint32_t pk0 = pack_bf16(ex2(s[0][2 * r] - mx[0][r]), ex2(s[0][2 * r + 1] - mx[0][r]));
          const uint32_t pk1 = pack_bf16(ex2(s[1][2 * r] - mx[1][r]), ex2(s[1][2 * r + 1] - mx[1][r]));
          const uint32_t a0 = pk0 & bandm, a1 = pk1 & bandm, a2 = pk0 & ~bandm, a3 = pk1 & ~bandm;
          float l[4] = {0.f, 0.f, 0.f, 0.f};
          mma16(l, a0, a1, a2, a3, sg[r], sg[r + 1]);
          const float i0 = rcp(l[0]), i1 = rcp(l[2]);
#pragma unroll
          for (int c = 0; c < 5; c++) {
            float d[4] = {0.f, 0.f, 0.f, 0.f};
            mma16(d, a0, a1, a2, a3, vf[c][2 * r], vf[c][2 * r + 1]);
            const bool h0 = c < 2 || (c == 2 && q < 2);
            const float i = h0 ? i0 : i1;
            ow[5 * p + c][r] = pack_bf16((h0 ? d[0] : d[2]) * i, (h0 ? d[1] : d[3]) * i);
          }
        }
#pragma unroll
        for (int c = 5 * p + p; c < 5 * p + 5; c += 2) ow[c][0] = lop3<0xEA>(ow[c][0], ~1u, tag);
        if (p == 0) {
          publish(0);
          publish(1);
          if (warp == X_PW) PROF(43);
          if (tag > 1) return;
        }
      }
    }
    if ((warp & 3) == 0) PROF2(7, wg);

    uint32_t w[10];
    float wr[20], ws = 0.f;
    uint4 *s2w, *s2r;
    {
      uint4 fa[4][7];
      const uint4* fp[7];
#pragma unroll
      for (int i = 1; i < 8; i++) fp[i - 1] = UNIT(obuf, oo ^ (i * 32));
      auto load_round = [&](int s) {
#pragma unroll
        for (int i = 0; i < 7; i++) fa[s & 3][i] = ld_msg(fp[i] + 256 * s);
      };
      auto desc = [&](int i, int s) { return make_desc(s16 + (kWo + i * 10240 + s * 2048) / 16, kWoTail - kWo + (i >> 2) * 10240 + (i & 3) * 32 - i * 10240, 1024, 1); };
      publish(2);
      mbar_wait(wg ? BAR(B_WO) : BAR(B_FULL + 3), 0);
      if (warp == X_PW) PROF(45);
      wgmma_fence();
#pragma unroll
      for (int s = 0; s < 5; s++) wgmma_n80_rs_ta0_tb1(acc, ow[2 * s][0], ow[2 * s][1], ow[2 * s + 1][0], ow[2 * s + 1][1], desc(0, s), 1);
      wgmma_commit();
      load_round(0);
      publish(3);
      load_round(1);
      publish(4);
      auto mma_round = [&](int s) {
#pragma unroll
        for (int i = 1; i < 8; i++) { const uint4& f = fa[s & 3][i - 1]; wgmma_n80_rs_ta0_tb1(acc, f.x, f.y, f.z, f.w, desc(i, s), 1); }
      };
      wait_round<0>(fa[0], fp, tag, spin);
      wait_round<4096>(fa[1], fp, tag, spin);
      if (warp == X_PW) PROF(42);
      bar_arrive(NB_OL, 288);
      wgmma_fence();
      load_round(2);
      load_round(3);
      mma_round(0);
      mma_round(1);
      wgmma_commit();
      wait_round<8192>(fa[2], fp, tag, spin);
      wait_round<12288>(fa[3], fp, tag, spin);
      if (warp == X_PW) PROF(44);
      if (warp == 0) bar_arrive(NB_RED, 64);
      wgmma_wait<0>();
      wgmma_fence();
      load_round(4);
      mma_round(2);
      mma_round(3);
      wgmma_commit();
      mbar_wait(BAR(B_TAIL), 1);
      wait_round<16384>(fa[0], fp, tag, spin);
      if (warp == X_PW) PROF(46);
      {
        const uint4 a = lds16(sb + kWr + q * 48), b = lds16(sb + kWr + q * 48 + 16), c = lds16(sb + kWr + q * 48 + 32);
        w[0] = a.x; w[1] = a.y; w[2] = a.z; w[3] = a.w; w[4] = b.x; w[5] = b.y; w[6] = b.z; w[7] = b.w; w[8] = c.x; w[9] = c.y;
        ws = __uint_as_float(c.z);
      }
      wgmma_fence();
      mma_round(4);
      wgmma_commit();
#pragma unroll
      for (int c = 0; c < 10; c++) { wr[2 * c] = bf_lo(w[c]); wr[2 * c + 1] = bf_hi(w[c]); pin(wr[2 * c]); pin(wr[2 * c + 1]); }
      uint32_t l2 = lane;
      pin(l2);
      s2w = UNIT(stat2, tw * 128 + hg * 16 + 8 * (l2 & 3) + (l2 >> 2)); s2r = UNIT(stat2, tw * 128 + l2 + (l2 & 16) * 3);
      pin(s2w); pin(s2r);
      if (__float_as_uint(ws) == 0) return;
      wgmma_wait<0>();
    }
    if ((warp & 3) == 0) PROF2(9, wg);

    {
      float u[4][3], t[2][3];
#pragma unroll
      for (int i = 0; i < 4; i++) { u[i][0] = acc[i]; u[i][1] = acc[i] * wr[i & 1]; u[i][2] = acc[i] * acc[i]; }
#pragma unroll
      for (int i = 4; i < 40; i++) { u[i & 3][0] += acc[i]; u[i & 3][1] = fmaf(acc[i], wr[(i >> 2) * 2 + (i & 1)], u[i & 3][1]); u[i & 3][2] = fmaf(acc[i], acc[i], u[i & 3][2]); }
#pragma unroll
      for (int i = 0; i < 6; i++) t[i / 3][i % 3] = u[2 * (i / 3)][i % 3] + u[2 * (i / 3) + 1][i % 3];
      float v[3];
#pragma unroll
      for (int i = 0; i < 3; i++) v[i] = (q & 1 ? t[1][i] : t[0][i]) + shx(q & 1 ? t[0][i] : t[1][i], 1);
#pragma unroll
      for (int i = 0; i < 3; i++) v[i] += shx(v[i], 2);
      st_msg_if(q < 2, s2w, __float_as_uint(v[0]), __float_as_uint(v[1]), __float_as_uint(v[2]), __float_as_uint(ws));
    }
    const uint32_t t_st2 = (uint32_t)clock64() + (X_SNS && !wg ? 150 : X_SWAIT);
    uint32_t hw[10][2];
#pragma unroll
    for (int c = 0; c < 10; c++) { hw[c][0] = pack_at(acc[4 * c], acc[4 * c + 1]); hw[c][1] = pack_at(acc[4 * c + 2], acc[4 * c + 3]); }
    if (warp == 0) PROF(11);
    uint32_t wa[5][2][4], wd[5][4];
    auto load_ffn = [&]() {
      mbar_wait(BAR(B_FFN), 0);
      const uint32_t row = 8 * (m >> 1) + l7;
      const uint32_t ag = sb + kGate + row * 64 + (((2 * wg + (m & 1)) ^ (l7 >> 1)) << 4), ad = sb + kDown + row * 128 + (((m & 1) ^ l7) << 4);
#pragma unroll
      for (int s = 0; s < 5; s++) {
        const uint32_t a = ag + (s < 4 ? (warp & 3) * 4096 + s * 1024 : 16384 + (warp & 3) * 1024);
        ldsm4t(wa[s][0][0], wa[s][0][1], wa[s][0][2], wa[s][0][3], a);
        ldsm4t(wa[s][1][0], wa[s][1][1], wa[s][1][2], wa[s][1][3], a + (kUp - kGate));
        ldsm4t(wd[s][0], wd[s][1], wd[s][2], wd[s][3],
               s < 4 ? (ad ^ (32 * s)) + warp * 2048 : (ad ^ (32 * (warp & 3))) + 16384 + wg * 2048);
      }
    };
    uint32_t wkey, z0, z1;
    {
      float mean, rstd;
      uint32_t tk = 4095 - 256 * rb - par - 32 * warp - 2 * (lane & 15);
      pin(tk);
      spin_until(t_st2);
      if (!wg) {
        mbar_wait(BAR(B_HALF + 2), 0);
        const uint32_t due = __float_as_uint(ldsf(sb + kMisc + 12)) + X_SNS;
        until_ns(due);
      }
#pragma unroll 1
      do {
        uint4 v[4];
#pragma unroll
        for (int i = 0; i < 4; i++) v[i] = ld_msg(s2r + 16 * i);
#define SUM4(c) ((__uint_as_float(v[0].c) + __uint_as_float(v[1].c)) + (__uint_as_float(v[2].c) + __uint_as_float(v[3].c)))
        float sm = SUM4(x), dt = SUM4(y), sq = SUM4(z), wt = SUM4(w);
#undef SUM4
        sm += shx(sm, 16); sq += shx(sq, 16); dt += shx(dt, 16); wt += shx(wt, 16);
        mean = sm * (1.f / 640);
        rstd = rsq(fmaxf(fmaf(-mean, mean, fmaf(sq, 1.f / 640, 1e-5f)), 1e-5f));
        const int sc = __float_as_int(fmaf(-mean, wt, dt) * rstd);
        const uint32_t low = min(min(v[0].w, v[1].w), min(v[2].w, v[3].w)) ? tk : ~0u;
        wkey = __reduce_max_sync(0xffffffffu, lop3<0xEA>(((uint32_t)(sc >> 31) | 0x80000000u) ^ sc, 0xFFFFF000u, low));
      } while (wkey == ~0u && --spin > 0);
      if (warp == 0) PROF(12);
      stsf(sb + kMisc + 16 + warp * 4, __uint_as_float(wkey));
      bar_arrive(NB_KEY, 288);
      if (wkey == 0) return;
      const uint32_t z = pack_bf16(mean, rstd);
      z0 = __shfl_sync(0xffffffffu, z, g); z1 = __shfl_sync(0xffffffffu, z, g + 8);
    }
    const uint32_t crow = (~wkey >> 1) & 15;
    const uint32_t ao = sb + kOutSt + warp * (16 * kPitch);
    {
      const uint32_t m0 = __byte_perm(z0, 0, 0x1010), r0 = __byte_perm(z0, 0, 0x3232), m1 = __byte_perm(z1, 0, 0x1010), r1 = __byte_perm(z1, 0, 0x3232);
      uint32_t cw[10];
#pragma unroll
      for (int c = 0; c < 10; c++) {
        const uint32_t l0 = mul2(sub2(hw[c][0], m0), r0), l1 = mul2(sub2(hw[c][1], m1), r1);
        asm("{\n.reg .pred p;\nsetp.ne.u32 p, %3, 0;\nselp.b32 %0, %1, %2, p;\n}" : "=r"(cw[c]) : "r"(l1), "r"(l0), "r"(crow & 8));
        hw[c][0] = add2(hw[c][0], l0); hw[c][1] = add2(hw[c][1], l1);
      }
      uint4* p = UNIT(cand, tw * 96 + hg * 12 + q);
      st_msg_if(g == (crow & 7), p, lop3<0xEA>(cw[0], ~1u, tag), cw[1], cw[2], cw[3]);
      st_msg_if(g == (crow & 7), p + 4, lop3<0xEA>(cw[4], ~1u, tag), cw[5], cw[6], cw[7]);
      st_msg_if(g == (crow & 7), p + 8, cw[8], cw[9], __byte_perm(cw[0], cw[4], 0x5410), tag);
#pragma unroll
      for (int i = 0; i < 5; i++) stsm4(ao + (lane & 15) * kPitch + (lane & 16) + 32 * i, hw[2 * i][0], hw[2 * i][1], hw[2 * i + 1][0], hw[2 * i + 1][1]);
      stsf(ao + 160, __uint_as_float(crow));
      bar_arrive(wg ? 0 : NB_GRID, 160);
    }
    uint32_t gkey;
    auto held_row = [&]() {
      const uint4 v = lds16(ao + crow * kPitch + lane * 16);
      const uint32_t cu = (lane < 8 ? 8 * hg : 56 + 2 * hg) + lane;
      uint4* p = at(gkey == wkey ? P.scr : reinterpret_cast<uint4*>(P.out), (gkey == wkey ? (uint32_t)(offsetof(Scratch, base) / 16) : (~wkey & 2047) * 80) + cu);
      st_msg_if(lane < 10, p, nz(v.x), nz(v.y), nz(v.z), nz(v.w));
    };
    if (fi < 96) {
      uint32_t rs;
      asm("mapa.shared::cluster.u32 %0, %1, %2;" : "=r"(rs) : "r"(sb), "r"(wg));
      uint32_t ax2 = sb + kSel + ((warp & 3) * 4 + q) * 48, rp = rs + kPart + (par * 4 + (warp & 3)) * 128 + lane * 4, rbar = rs + kBars + 8 * (B_FULL + 2);
      uint32_t ap = sb + kPart + lane * 4, sl = 8 * q, em = g & 1 ? 0u : ~0u;
      uint4* yp = UNIT(ypart, fi * 192 + q * 64 + warp * 8 + g);
      pin(ax2); pin(rp); pin(rbar); pin(ap); pin(sl); pin(em); pin(yp);
      load_ffn();
      if (wkey == 1) return;
      bar_sync(NB_KEY + 1, 320);
      const uint4 v0 = lds16(ax2), v1 = lds16(ax2 + 16);
      const uint2 v2 = lds8(ax2 + 32);
      gkey = __float_as_uint(ldsf(sb + kMisc + 8));
      if (warp == 0) PROF(16);
      const uint32_t xs[10] = {v0.x, v0.y, v0.z, v0.w, v1.x, v1.y, v1.z, v1.w, v2.x, v2.y};
      float d[4][4];
#pragma unroll
      for (int i = 0; i < 16; i++) d[i >> 2][i & 3] = 0.f;
#pragma unroll
      for (int s = 0; s < 5; s++) {
        mma16(d[s & 1], wa[s][0][0], wa[s][0][1], wa[s][0][2], wa[s][0][3], xs[2 * s], xs[2 * s + 1]);
        mma16(d[2 + (s & 1)], wa[s][1][0], wa[s][1][1], wa[s][1][2], wa[s][1][3], xs[2 * s], xs[2 * s + 1]);
      }
      asm volatile("{\n.reg .pred p;\nsetp.eq.u32 p, %6, 0;\n@p st.async.weak.shared::cluster.mbarrier::complete_tx::bytes.v4.f32 [%0], {%1, %2, %3, %4}, [%5];\n}"
                   ::"r"(rp), "f"(d[0][0] + d[1][0]), "f"(d[0][2] + d[1][2]), "f"(d[2][0] + d[3][0]), "f"(d[2][2] + d[3][2]), "r"(rbar), "r"(sl) : "memory");
      mbar_wait(BAR(B_FULL + 2), 0);
      float pv[8];
#pragma unroll
      for (int i = 0; i < 8; i++) pv[i] = ldsf(ap + i * 128);
      const float gv = bf_round(((pv[0] + pv[1]) + (pv[2] + pv[3])) + ((pv[4] + pv[5]) + (pv[6] + pv[7])));
      const float hid = (gv * shx(gv, 2)) * sigmoid(gv);
      const uint32_t h0 = pack_bf16(__shfl_sync(0xffffffffu, hid, sl), __shfl_sync(0xffffffffu, hid, sl + 4));
      const uint32_t h1 = pack_bf16(__shfl_sync(0xffffffffu, hid, sl + 1), __shfl_sync(0xffffffffu, hid, sl + 5));
      float y[3][4];
#pragma unroll
      for (int n = 0; n < 5; n++) {
        const int t = n < 3 ? 2 * n : 2 * n - 5;
        if (n < 3) y[n][0] = y[n][1] = y[n][2] = y[n][3] = 0.f;
        mma16(y[t >> 1], wd[t][0], wd[t][1], wd[t][2], wd[t][3], n < 3 ? h0 & em : h0 & ~em, n < 3 ? h1 & em : h1 & ~em);
      }
      uint32_t yu[4];
#pragma unroll
      for (int e = 0; e < 4; e++) yu[e] = __float_as_uint(sl == 8 ? y[1][e] : sl ? y[2][e] : y[0][e]);
      st_msg_if(sl < 24, yp, nz(yu[0]), yu[1], yu[2], yu[3]);
      if (warp == 0) PROF(17);
    } else {
      bar_sync(NB_KEY + 1, 320);
      gkey = __float_as_uint(ldsf(sb + kMisc + 8));
    }
    const uint32_t go = (uint32_t)clock64() + X_YWAIT;
    held_row();
    if (fi < 96 && warp == 0) {
      const uint32_t ch = 4 * (fi >> 5) + (lane & 2) + ((lane >> 2) & 1), col = col_of((fi >> 2) & 7, min(ch, 9u)) + 2 * (fi & 3);
      const float sig = bf_round(sigmoid(bf_round(__uint_as_float(((uint32_t)((int)~gkey >> 31) | 0x80000000u) ^ gkey))));
      const uint4* p = UNIT(ypart, (lane >> 1) * 192 + 2 * fi + (lane & 1));
      const uint32_t* pb = WORD(base, col >> 1);
      uint16_t* po = at(reinterpret_cast<uint16_t*>(P.out), (~gkey & 2047) * 640 + col + (lane & 1));
      uint32_t o;
      bool ok;
      spin_until(go);
      const uint32_t gn = __float_as_uint(ldsf(sb + kMisc + 12)) + X_YNS;
      until_ns(gn);
#pragma unroll 1
      do {
        uint4 u[6];
        const uint32_t bw = ld_word(pb);
#pragma unroll
        for (int i = 0; i < 6; i++) u[i] = ld_msg(p + 16 * 192 * i);
        ok = all(min(min(min(u[0].x, u[1].x), min(u[2].x, u[3].x)), min(min(u[4].x, u[5].x), bw)));
#define SUM6(c) (((__uint_as_float(u[0].c) + __uint_as_float(u[1].c)) + (__uint_as_float(u[2].c) + __uint_as_float(u[3].c))) + (__uint_as_float(u[4].c) + __uint_as_float(u[5].c)))
        const float y0 = SUM6(x), y1 = SUM6(y), y2 = SUM6(z), y3 = SUM6(w);
#undef SUM6
        const float ya = (lane & 2 ? y1 : y0) + shx(lane & 2 ? y0 : y1, 2), yb = (lane & 2 ? y3 : y2) + shx(lane & 2 ? y2 : y3, 2);
        float y = (lane & 4 ? yb : ya) + shx(lane & 4 ? ya : yb, 4);
        y = (y + shx(y, 8)) + (shx(y, 16) + shx(y, 24));
        o = pack_bf16(fmaf(y, sig, bf_hi(bw << (~lane & 1) * 16)), 0.f);
        asm volatile("{\n.reg .pred p;\nsetp.ne.u32 p, %2, 0;\n@p st.global.u16 [%0], %1;\n}" ::"l"(po), "h"((uint16_t)o), "r"((uint32_t)(ok && lane < 8 && ch < 10)) : "memory");
      } while (!ok && --spin > 0);
    }
  }
#undef BAR
#undef UNIT
#undef WORD
}

typedef CUresult (*EncodeTiledFn)(CUtensorMap*, CUtensorMapDataType, cuuint32_t, void*, const cuuint64_t*, const cuuint64_t*, const cuuint32_t*,
                                  const cuuint32_t*, CUtensorMapInterleave, CUtensorMapSwizzle, CUtensorMapL2promotion, CUtensorMapFloatOOBfill);

void make_map(EncodeTiledFn fn, CUtensorMap* m, const void* base, int rank, const cuuint64_t* dims, const cuuint64_t* strides, const cuuint32_t* box,
              CUtensorMapSwizzle swz) {
  const cuuint32_t es[5] = {1, 1, 1, 1, 1};
  fn(m, CU_TENSOR_MAP_DATA_TYPE_BFLOAT16, rank, const_cast<void*>(base), dims, strides, box, es, CU_TENSOR_MAP_INTERLEAVE_NONE, swz,
     CU_TENSOR_MAP_L2_PROMOTION_L2_128B, CU_TENSOR_MAP_FLOAT_OOB_FILL_NONE);
}

}

extern "C" void kernel_launch(void* const* d_in, const int* in_sizes, int n_in, void* d_out, int out_size) {
  (void)in_sizes; (void)n_in; (void)out_size;
  static EncodeTiledFn fn = nullptr;
  static int num_sms = 0;
  static uint4* scr = nullptr;
  static unsigned* count = nullptr;
  if (!fn) {
    int reserved = 0;
    cudaDeviceGetAttribute(&num_sms, cudaDevAttrMultiProcessorCount, 0);
    cudaDeviceGetAttribute(&reserved, cudaDevAttrReservedSharedMemoryPerBlock, 0);
    if (reserved != 1024) num_sms = 0;
    cudaGetSymbolAddress(reinterpret_cast<void**>(&scr), g_scr);
    cudaGetSymbolAddress(reinterpret_cast<void**>(&count), g_count);
    void* p = nullptr;
    cudaDriverEntryPointQueryResult qr;
    cudaGetDriverEntryPoint("cuTensorMapEncodeTiled", &p, cudaEnableDefault, &qr);
    fn = reinterpret_cast<EncodeTiledFn>(p);
    cudaFuncSetAttribute(fused_block_kernel<true>, cudaFuncAttributeMaxDynamicSharedMemorySize, kSmemBytes);
    cudaFuncSetAttribute(fused_block_kernel<false>, cudaFuncAttributeMaxDynamicSharedMemorySize, kSmemBytes);
  }
  Params P;
  P.x = static_cast<const uint8_t*>(d_in[0]);
  P.wqkv = static_cast<const uint8_t*>(d_in[1]);
  P.wo = static_cast<const uint8_t*>(d_in[2]);
  P.wr = static_cast<const uint32_t*>(d_in[4]);
  P.scr = scr;
  P.count = count;
  P.wgate = static_cast<const uint8_t*>(d_in[5]);
  P.wup = static_cast<const uint8_t*>(d_in[6]);
  P.wdown = static_cast<const uint8_t*>(d_in[7]);
  P.out = static_cast<uint8_t*>(d_out);
  { const cuuint64_t d[2] = {1280, 1024}, s[1] = {2560}; const cuuint32_t bx[2] = {64, 64};
    make_map(fn, &P.mx, d_in[0], 2, d, s, bx, CU_TENSOR_MAP_SWIZZLE_128B); }
  { const cuuint64_t d[3] = {640, 640, 3}, s[2] = {3840, 1280}; const cuuint32_t bx[3] = {64, 16, 3}, bx2[3] = {16, 16, 3};
    make_map(fn, &P.mw64, d_in[1], 3, d, s, bx, CU_TENSOR_MAP_SWIZZLE_128B);
    make_map(fn, &P.mw16, d_in[1], 3, d, s, bx2, CU_TENSOR_MAP_SWIZZLE_32B); }
  { const cuuint64_t d[2] = {640, 640}, s[1] = {1280}; const cuuint32_t bx[2] = {64, 80};
    make_map(fn, &P.mwo, d_in[2], 2, d, s, bx, CU_TENSOR_MAP_SWIZZLE_128B); }
  { const cuuint64_t d[3] = {640, 8, 80}, s[2] = {102400, 1280}; const cuuint32_t bx[3] = {16, 4, 20};
    make_map(fn, &P.mtail, d_in[2], 3, d, s, bx, CU_TENSOR_MAP_SWIZZLE_NONE); }
  { const cuuint64_t d[2] = {1536, 640}, s[1] = {3072}; const cuuint32_t bx[2] = {32, 64};
    make_map(fn, &P.mgate, d_in[5], 2, d, s, bx, CU_TENSOR_MAP_SWIZZLE_64B);
    make_map(fn, &P.mup, d_in[6], 2, d, s, bx, CU_TENSOR_MAP_SWIZZLE_64B); }
  { const cuuint64_t d[3] = {64, 1536, 10}, s[2] = {1280, 128}; const cuuint32_t bx[3] = {64, 16, 2};
    make_map(fn, &P.mdown, d_in[7], 3, d, s, bx, CU_TENSOR_MAP_SWIZZLE_128B); }
  if (num_sms == 132) fused_block_kernel<true><<<132, 384, kSmemBytes, cudaStreamPerThread>>>(P.x, P.wqkv, P.wqkv - P.x, P);
  else fused_block_kernel<false><<<132, 384, kSmemBytes, cudaStreamPerThread>>>(P.x, P.wqkv, P.wqkv - P.x, P);
}
```
